```python
import torch

def _softmax(x, axis=-1):
    return torch.softmax(x, dim=axis)

def _gelu(x):
    return torch.nn.functional.gelu(x, approximate='tanh')

def _silu(x):
    return torch.nn.functional.silu(x)

def _sigmoid(x):
    return torch.sigmoid(x)

def _layernorm(x, axis=-1, eps=1e-05):
    m = x.mean(dim=axis, keepdim=True)
    v = x.var(dim=axis, keepdim=True, unbiased=False)
    return (x - m) / torch.sqrt(v + eps)

def _scatter_add(tgt, idx, src, axis=0):
    return tgt.clone().index_add_(axis, idx, src)

def _segment_sum(src, seg, n):
    out = torch.zeros((n,) + src.shape[1:], dtype=src.dtype)
    return out.index_add_(0, seg, src)

def _pad(x, pw):
    flat = tuple((v for pair in reversed(pw) for v in pair))
    return torch.nn.functional.pad(x, flat)
kernel_name = 'adaLN_cond__gqa_block_cached__glu_gated_swiglu__decode'

def setup_inputs():

    _w = lambda a: (lambda t: t.to(torch.bfloat16) if t.is_floating_point() else t)(torch.as_tensor(a))

    def _A_setup():
        B, Sq, D = (2, 1, 576)
        Hq, Hkv, Sk, Dh = (32, 16, 8192, 128)
        assert Hq % Hkv == 0, (Hq, Hkv)
        return {'x': _w((lambda *s: torch.randn(*s, dtype=torch.bfloat16) * 0.1)(B, Sq, D)), 'k_cache': _w((lambda *s: torch.randn(*s, dtype=torch.bfloat16) * 0.8)(B, Hkv, Sk, Dh)), 'v_cache': _w((lambda *s: torch.randn(*s, dtype=torch.bfloat16) * 3.2)(B, Hkv, Sk, Dh)), 'wq': _w((lambda *s: torch.randn(*s, dtype=torch.bfloat16) * 0.8)(D, Hq * Dh) * D ** (-0.5)), 'wo': _w((lambda *s: torch.randn(*s, dtype=torch.bfloat16) * 3.2)(Hq * Dh, D) * (Hq * Dh) ** (-0.5))}
    _A_in = _A_setup()

    def _B_setup():
        B, S, D, F = (2, 1, 576, 4608)
        return {'x': _w((lambda *s: torch.randn(*s, dtype=torch.bfloat16) * 0.1)(B, S, D)), 'w1': _w((lambda *s: torch.randn(*s, dtype=torch.bfloat16) * 3.2)(D, F) * (2.0 / D) ** 0.5), 'w3': _w((lambda *s: torch.randn(*s, dtype=torch.bfloat16) * 3.2)(D, F) * (2.0 / D) ** 0.5), 'w2': _w((lambda *s: torch.randn(*s, dtype=torch.bfloat16) * 3.2)(F, D) * (2.0 / F) ** 0.5)}
    _B_in = _B_setup()
    return {'A_x': _A_in['x'], 'A_k_cache': _A_in['k_cache'], 'A_v_cache': _A_in['v_cache'], 'A_wq': _A_in['wq'], 'A_wo': _A_in['wo'], 'B_x': _B_in['x'], 'B_w1': _B_in['w1'], 'B_w3': _B_in['w3'], 'B_w2': _B_in['w2'], 'c': _w((lambda *s: torch.randn(*s, dtype=torch.bfloat16) * 0.4)(2, 576) * 8.0), 'w_mod': _w((lambda *s: torch.randn(*s, dtype=torch.bfloat16) * 0.4)(576, 6 * 576) * 576 ** (-0.5) * 8.0)}

def reference(A_x, A_k_cache, A_v_cache, A_wq, A_wo, B_x, B_w1, B_w3, B_w2, c, w_mod):

    def _A_ref(x, k_cache, v_cache, wq, wo):
        B, Sq, D = x.shape
        Hq, Dh = (32, 128)
        Hkv = k_cache.shape[1]
        rep = Hq // Hkv
        q = (lambda x, *d: x.permute(*d))((x @ wq).reshape(B, Sq, Hq, Dh), 0, 2, 1, 3)
        k = (lambda x, n, axis: torch.repeat_interleave(x, n, dim=axis))(k_cache, rep, axis=1)
        v = (lambda x, n, axis: torch.repeat_interleave(x, n, dim=axis))(v_cache, rep, axis=1)
        scores = torch.einsum('bhqd,bhkd->bhqk', q, k) * Dh ** (-0.5)
        p = _softmax(scores, axis=-1)
        o = torch.einsum('bhqk,bhkd->bhqd', p, v)
        return (lambda x, *d: x.permute(*d))(o, 0, 2, 1, 3).reshape(B, Sq, Hq * Dh) @ wo

    def _B_ref(x, w1, w3, w2):
        gate = torch.einsum('bsd,df->bsf', x, w1)
        up = torch.einsum('bsd,df->bsf', x, w3)
        h = _silu(gate) * up
        out = torch.einsum('bsf,fd->bsd', h, w2)
        return out
    x = A_x
    mod = (_silu(c) @ w_mod).reshape(c.shape[0], 6, 1, -1)
    sa, ca, ga, sb, cb, gb = (mod[:, 0].clone(), mod[:, 1].clone(), mod[:, 2].clone(), mod[:, 3].clone(), mod[:, 4].clone(), mod[:, 5].clone())
    h = _layernorm(x, axis=-1) * (1 + ca) + sa
    x = x + ga * _A_ref(h, A_k_cache, A_v_cache, A_wq, A_wo)
    h = _layernorm(x, axis=-1) * (1 + cb) + sb
    x = x + gb * _B_ref(h, B_w1, B_w3, B_w2)
    return x
```

```cpp
#include <cuda_runtime.h>
#include <cuda_bf16.h>
#include <cuda.h>
#include <stdint.h>

namespace {

typedef __nv_bfloat16 bf16;

constexpr int kD    = 576;
constexpr int kF    = 4608;
constexpr int kQD   = 4096;
constexpr int kMOD  = 6 * kD;
constexpr int kSK   = 8192;
constexpr int NCTA  = 128;
constexpr int NCONS = 256;
constexpr int NTHR  = 288;
constexpr int SLOT  = 16384;
constexpr int NS    = 12;
constexpr int NKV   = 64;
constexpr int NW    = 13;
constexpr int NITEM = NKV + NW;
#define DEPTH 4
constexpr int NOWN  = 72;

constexpr int WPITCH = 1168;
constexpr int OFF_WO = 0;
constexpr int OFF_W1 = OFF_WO + 32 * WPITCH;
constexpr int OFF_W3 = OFF_W1 + 576 * 80;
constexpr int OFF_W2 = OFF_W3 + 576 * 80;
constexpr int WEND   = OFF_W2 + 36 * WPITCH;
static_assert(WEND <= NS * SLOT, "weights must fit in the ring");
static_assert(OFF_W1 % 128 == 0 && OFF_W3 % 128 == 0, "TMA dst alignment");

constexpr int SM_RING = 0;
constexpr int SM_BAR  = NS * SLOT;
constexpr int SM_U    = SM_BAR + 1152;
constexpr int SM_CB1  = SM_U + 9216;
constexpr int SM_SB   = SM_CB1 + 4608;
constexpr int SM_RED  = SM_SB + 4608;
constexpr int SM_QS   = SM_RED + 2560;
constexpr int SM_ML   = SM_QS + 512;
constexpr int SM_OS   = SM_ML + 128;
constexpr int SM_HH   = SM_OS + 128;
constexpr int SM_OWN  = SM_HH + 192;
constexpr int SM_TAG  = SM_OWN + 256;
constexpr int SM_TOTAL = SM_TAG + 64;
static_assert(SM_TOTAL <= 232448, "smem");
static_assert((NITEM + NKV) * 8 <= 1152, "barrier region");

constexpr unsigned EMPTY = 0xFFFFFFFFu;
constexpr int SPIN_LIMIT = 1 << 22;

__device__ unsigned g_arrive;
__device__ __align__(128) uint2 g_mod[2 * (kMOD / 2)];
__device__ __align__(128) uint2 g_q[2 * (kQD / 2)];
__device__ __align__(128) float g_x3[NCTA * 8 * 36];
__device__ __align__(128) float g_x4[NOWN * NCTA * 16];
__device__ __align__(128) unsigned g_x5[kD];
__device__ __align__(128) float g_x6[NOWN * NCTA * 16];
#define TS(i) do {} while (0)

__device__ __forceinline__ uint32_t smem_u32(const void* p) { return (uint32_t)__cvta_generic_to_shared(p); }
__device__ __forceinline__ void mbar_init(uint32_t bar, uint32_t cnt) {
    asm volatile("mbarrier.init.shared::cta.b64 [%0], %1;" ::"r"(bar), "r"(cnt) : "memory");
}
__device__ __forceinline__ void mbar_expect_tx(uint32_t bar, uint32_t bytes) {
    asm volatile("mbarrier.arrive.expect_tx.shared::cta.b64 _, [%0], %1;" ::"r"(bar), "r"(bytes) : "memory");
}
__device__ __forceinline__ void mbar_arrive(uint32_t bar) {
    asm volatile("mbarrier.arrive.shared::cta.b64 _, [%0];" ::"r"(bar) : "memory");
}
__device__ __forceinline__ void mbar_wait(uint32_t bar) {
    uint32_t ok;
    int spin = 0;
    do {
        asm volatile("{\n.reg .pred p;\nmbarrier.try_wait.parity.shared::cta.b64 p, [%1], 0;\nselp.u32 %0, 1, 0, p;\n}"
                     : "=r"(ok) : "r"(bar) : "memory");
        if (!ok && ++spin > SPIN_LIMIT) __trap();
    } while (!ok);
}
__device__ __forceinline__ void bulk_load(uint32_t dst, const void* src, uint32_t bytes, uint32_t bar, uint64_t pol) {
    asm volatile("cp.async.bulk.shared::cluster.global.mbarrier::complete_tx::bytes.L2::cache_hint [%0], [%1], %2, [%3], %4;"
                 ::"r"(dst), "l"(src), "r"(bytes), "r"(bar), "l"(pol) : "memory");
}
__device__ __forceinline__ void tma2d(uint32_t dst, const CUtensorMap* tm, int c0, int c1, uint32_t bar) {
    asm volatile("cp.async.bulk.tensor.2d.shared::cluster.global.mbarrier::complete_tx::bytes [%0], [%1, {%3, %4}], [%2];"
                 ::"r"(dst), "l"(tm), "r"(bar), "r"(c0), "r"(c1) : "memory");
}
__device__ __forceinline__ void cons_bar() { asm volatile("bar.sync 1, 256;" ::: "memory"); }

__device__ __forceinline__ uint4 ldg_nc(const void* p) {
    uint4 v;
    asm volatile("ld.global.nc.L1::no_allocate.v4.u32 {%0,%1,%2,%3}, [%4];" : "=r"(v.x), "=r"(v.y), "=r"(v.z), "=r"(v.w) : "l"(p));
    return v;
}
__device__ __forceinline__ uint4 ld_rlx4(const void* p) {
    uint4 v;
    asm volatile("ld.relaxed.gpu.global.v4.u32 {%0,%1,%2,%3}, [%4];" : "=r"(v.x), "=r"(v.y), "=r"(v.z), "=r"(v.w) : "l"(p) : "memory");
    return v;
}
__device__ __forceinline__ uint2 ld_rlx2(const void* p) {
    uint2 v;
    asm volatile("ld.relaxed.gpu.global.v2.u32 {%0,%1}, [%2];" : "=r"(v.x), "=r"(v.y) : "l"(p) : "memory");
    return v;
}
__device__ __forceinline__ unsigned ld_rlx1(const void* p) {
    unsigned v;
    asm volatile("ld.relaxed.gpu.global.u32 %0, [%1];" : "=r"(v) : "l"(p) : "memory");
    return v;
}
__device__ __forceinline__ unsigned ld_acq1(const void* p) {
    unsigned v;
    asm volatile("ld.acquire.gpu.global.u32 %0, [%1];" : "=r"(v) : "l"(p) : "memory");
    return v;
}
__device__ __forceinline__ void st_rlx4(void* p, uint4 v) {
    asm volatile("st.relaxed.gpu.global.v4.u32 [%0], {%1,%2,%3,%4};" ::"l"(p), "r"(v.x), "r"(v.y), "r"(v.z), "r"(v.w) : "memory");
}
__device__ __forceinline__ void st_rlx2(void* p, uint32_t a, uint32_t b) {
    asm volatile("st.relaxed.gpu.global.v2.u32 [%0], {%1,%2};" ::"l"(p), "r"(a), "r"(b) : "memory");
}
__device__ __forceinline__ void st_rlx_unit(void* p, uint32_t a, uint32_t b) {
    unsigned long long v = (unsigned long long)a | ((unsigned long long)b << 32);
    asm volatile("st.relaxed.gpu.global.u64 [%0], %1;" ::"l"(p), "l"(v) : "memory");
}
__device__ __forceinline__ uint4 ld_rlx_units2(const void* p) {
    unsigned long long a, b;
    asm volatile("ld.relaxed.gpu.global.v2.u64 {%0,%1}, [%2];" : "=l"(a), "=l"(b) : "l"(p) : "memory");
    return make_uint4((uint32_t)a, (uint32_t)(a >> 32), (uint32_t)b, (uint32_t)(b >> 32));
}
__device__ __forceinline__ void st_rlx1(void* p, uint32_t a) {
    asm volatile("st.relaxed.gpu.global.u32 [%0], %1;" ::"l"(p), "r"(a) : "memory");
}
__device__ __forceinline__ uint32_t canon(float f) {
    uint32_t u = __float_as_uint(f);
    return u == EMPTY ? 0x7FFFFFFFu : u;
}
__device__ __forceinline__ float bfr(float x) { return __bfloat162float(__float2bfloat16_rn(x)); }
__device__ __forceinline__ uint32_t pack_bf(float lo, float hi) {
    __nv_bfloat162 v = __floats2bfloat162_rn(lo, hi);
    return *reinterpret_cast<uint32_t*>(&v);
}
__device__ __forceinline__ float bf_lo(uint32_t u) { return __uint_as_float(u << 16); }
__device__ __forceinline__ float bf_hi(uint32_t u) { return __uint_as_float(u & 0xFFFF0000u); }
__device__ __forceinline__ float ex2(float x) {
    float y;
    asm("ex2.approx.ftz.f32 %0, %1;" : "=f"(y) : "f"(x));
    return y;
}
__device__ __forceinline__ float silu_f(float x) { return x / (1.0f + expf(-x)); }

__device__ __forceinline__ void ldsm4(uint32_t a, uint32_t& r0, uint32_t& r1, uint32_t& r2, uint32_t& r3) {
    asm volatile("ldmatrix.sync.aligned.m8n8.x4.shared.b16 {%0,%1,%2,%3}, [%4];" : "=r"(r0), "=r"(r1), "=r"(r2), "=r"(r3) : "r"(a) : "memory");
}
__device__ __forceinline__ void ldsm4t(uint32_t a, uint32_t& r0, uint32_t& r1, uint32_t& r2, uint32_t& r3) {
    asm volatile("ldmatrix.sync.aligned.m8n8.x4.trans.shared.b16 {%0,%1,%2,%3}, [%4];" : "=r"(r0), "=r"(r1), "=r"(r2), "=r"(r3) : "r"(a) : "memory");
}
__device__ __forceinline__ void ldsm2t(uint32_t a, uint32_t& r0, uint32_t& r1) {
    asm volatile("ldmatrix.sync.aligned.m8n8.x2.trans.shared.b16 {%0,%1}, [%2];" : "=r"(r0), "=r"(r1) : "r"(a) : "memory");
}
__device__ __forceinline__ void mma16816(float* c, uint32_t a0, uint32_t a1, uint32_t a2, uint32_t a3, uint32_t b0, uint32_t b1) {
    asm volatile("mma.sync.aligned.m16n8k16.row.col.f32.bf16.bf16.f32 {%0,%1,%2,%3}, {%4,%5,%6,%7}, {%8,%9}, {%0,%1,%2,%3};"
                 : "+f"(c[0]), "+f"(c[1]), "+f"(c[2]), "+f"(c[3])
                 : "r"(a0), "r"(a1), "r"(a2), "r"(a3), "r"(b0), "r"(b1));
}
__device__ __forceinline__ int phys_slot(int item) { return (item + (NS - NKV % NS)) % NS; }

__device__ __forceinline__ void gemv_regs(const uint4 (&w)[9], const float* act, float* red, int tid) {
    const int rg = tid >> 2, lane = tid & 31, warp = tid >> 5;
    float acc[16];
#pragma unroll
    for (int k = 0; k < 16; k++) acc[k] = 0.f;
#pragma unroll
    for (int i = 0; i < 9; i++) {
        const float a0 = act[rg + 64 * i], a1 = act[kD + rg + 64 * i];
        const uint32_t ww[4] = {w[i].x, w[i].y, w[i].z, w[i].w};
#pragma unroll
        for (int k = 0; k < 4; k++) {
            const float lo = bf_lo(ww[k]), hi = bf_hi(ww[k]);
            acc[2 * k] = fmaf(a0, lo, acc[2 * k]);
            acc[2 * k + 1] = fmaf(a0, hi, acc[2 * k + 1]);
            acc[8 + 2 * k] = fmaf(a1, lo, acc[8 + 2 * k]);
            acc[8 + 2 * k + 1] = fmaf(a1, hi, acc[8 + 2 * k + 1]);
        }
    }
    const bool b4 = lane & 16, b3 = lane & 8, b2 = lane & 4;
    float v8[8], v4[4], v2[2];
#pragma unroll
    for (int k = 0; k < 8; k++) {
        const float keep = b4 ? acc[8 + k] : acc[k], send = b4 ? acc[k] : acc[8 + k];
        v8[k] = keep + __shfl_xor_sync(0xffffffffu, send, 16);
    }
#pragma unroll
    for (int k = 0; k < 4; k++) {
        const float keep = b3 ? v8[4 + k] : v8[k], send = b3 ? v8[k] : v8[4 + k];
        v4[k] = keep + __shfl_xor_sync(0xffffffffu, send, 8);
    }
#pragma unroll
    for (int k = 0; k < 2; k++) {
        const float keep = b2 ? v4[2 + k] : v4[k], send = b2 ? v4[k] : v4[2 + k];
        v2[k] = keep + __shfl_xor_sync(0xffffffffu, send, 4);
    }
    const int col = (lane & 3) * 8 + (b3 ? 4 : 0) + (b2 ? 2 : 0);
    *reinterpret_cast<float2*>(red + warp * 64 + (b4 ? 32 : 0) + col) = make_float2(v2[0], v2[1]);
}

__device__ __forceinline__ void ln_stats(const float* v, int lane, float& mean_bf, float& sd_bf) {
    float s = 0.f, r[18];
#pragma unroll
    for (int i = 0; i < 18; i++) { r[i] = v[lane + 32 * i]; s += r[i]; }
#pragma unroll
    for (int o = 16; o; o >>= 1) s += __shfl_xor_sync(0xffffffffu, s, o);
    const float mean = s * (1.0f / kD);
    float q = 0.f;
#pragma unroll
    for (int i = 0; i < 18; i++) { const float d = r[i] - mean; q = fmaf(d, d, q); }
#pragma unroll
    for (int o = 16; o; o >>= 1) q += __shfl_xor_sync(0xffffffffu, q, o);
    mean_bf = bfr(mean);
    sd_bf = bfr(sqrtf(bfr(bfr(q * (1.0f / kD)) + 1e-5f)));
}

__device__ __forceinline__ float owner_reduce(const float* inbox, float* red, int tid) {
    const int lane = tid & 31, warp = tid >> 5;
    const float* p0 = inbox + (tid >> 2) * 16 + (tid & 3) * 4;
    const float* p1 = p0 + 64 * 16;
    uint4 a, b;
    int spin = 0;
    while (true) {
        a = ld_rlx4(p0);
        b = ld_rlx4(p1);
        const bool ok = a.x != EMPTY && a.y != EMPTY && a.z != EMPTY && a.w != EMPTY &&
                        b.x != EMPTY && b.y != EMPTY && b.z != EMPTY && b.w != EMPTY;
        if (ok) break;
        if (++spin > SPIN_LIMIT) __trap();
    }
    float v[4] = {__uint_as_float(a.x) + __uint_as_float(b.x), __uint_as_float(a.y) + __uint_as_float(b.y),
                  __uint_as_float(a.z) + __uint_as_float(b.z), __uint_as_float(a.w) + __uint_as_float(b.w)};
    __syncwarp();
#pragma unroll
    for (int o = 4; o <= 16; o <<= 1)
#pragma unroll
        for (int k = 0; k < 4; k++) v[k] += __shfl_xor_sync(0xffffffffu, v[k], o);
    if (lane < 4) *reinterpret_cast<float4*>(red + warp * 16 + lane * 4) = make_float4(v[0], v[1], v[2], v[3]);
    cons_bar();
    float s = 0.f;
    if (tid < 16) {
#pragma unroll
        for (int w = 0; w < 8; w++) s += red[w * 16 + tid];
    }
    return s;
}

__global__ void __launch_bounds__(NTHR, 1)
fused_kernel(const __grid_constant__ CUtensorMap tm_w1, const __grid_constant__ CUtensorMap tm_w3,
             const bf16* __restrict__ x, const bf16* __restrict__ kc, const bf16* __restrict__ vc,
             const bf16* __restrict__ wq, const bf16* __restrict__ wo, const bf16* __restrict__ w2,
             const bf16* __restrict__ cvec, const bf16* __restrict__ wmod, bf16* __restrict__ out) {
    extern __shared__ __align__(1024) unsigned char smem[];
    const uint32_t sbase = smem_u32(smem);
    const uint32_t bar_full = sbase + SM_BAR, bar_empty = bar_full + NITEM * 8;
    const int tid = threadIdx.x, lane = tid & 31, warp = tid >> 5;
    const int j = blockIdx.x;
    const int grp = j >> 3, rnk = j & 7;
    const int bb = rnk >> 2, sp = rnk & 3;

    if (warp == 8) {
        for (int i = lane; i < NITEM + NKV; i += 32) mbar_init(bar_full + i * 8, 1);
        asm volatile("fence.mbarrier_init.release.cluster;" ::: "memory");
        asm volatile("fence.proxy.async.shared::cta;" ::: "memory");
        __syncwarp();
        uint64_t pol;
        asm volatile("createpolicy.fractional.L2::evict_first.b64 %0, 1.0;" : "=l"(pol));
        const size_t kvoff = ((size_t)(bb * 16 + grp) * kSK + (size_t)sp * 2048) * 128;
        const unsigned char* kp = reinterpret_cast<const unsigned char*>(kc + kvoff);
        const unsigned char* vp = reinterpret_cast<const unsigned char*>(vc + kvoff);
        if (lane == 0) {
#pragma unroll
            for (int i = 0; i < DEPTH; i++) {
                mbar_expect_tx(bar_full + i * 8, SLOT);
                bulk_load(sbase + phys_slot(i) * SLOT, ((i & 1) ? vp : kp) + (size_t)(i >> 1) * SLOT, SLOT, bar_full + i * 8, pol);
            }
        }
        __syncthreads();
        if (lane == 0) {
            asm volatile("prefetch.tensormap [%0];" ::"l"(&tm_w1) : "memory");
            asm volatile("prefetch.tensormap [%0];" ::"l"(&tm_w3) : "memory");
            for (int i = DEPTH; i < NKV; i++) {
                if (i >= NS) mbar_wait(bar_empty + (i - NS) * 8);
                mbar_wait(bar_full + (i - DEPTH) * 8);
                mbar_expect_tx(bar_full + i * 8, SLOT);
                bulk_load(sbase + phys_slot(i) * SLOT, ((i & 1) ? vp : kp) + (size_t)(i >> 1) * SLOT, SLOT, bar_full + i * 8, pol);
            }
        }
        __syncwarp();
        TS(8);
        int freed = 0;
        const int c0 = (36 * j) & ~7;
#pragma unroll 1
        for (int wi = 0; wi < NW; wi++) {
            const int item = NKV + wi;
            int dst, bytes, end;
            if (wi < 2)       { dst = OFF_WO + wi * 16 * WPITCH; bytes = 16 * 1152; end = dst + 16 * WPITCH; }
            else if (wi < 10) { const int q = (wi - 2) >> 1; dst = (((wi - 2) & 1) ? OFF_W3 : OFF_W1) + q * 144 * 80; bytes = 144 * 80; end = dst + bytes; }
            else              { const int q = wi - 10; dst = OFF_W2 + q * 16 * WPITCH; bytes = (q < 2 ? 16 : 4) * 1152; end = dst + (q < 2 ? 16 : 4) * WPITCH; }
            const int need = (end - 1) / SLOT + 1;
            while (freed < need) { mbar_wait(bar_empty + (NKV - NS + freed) * 8); freed++; }
            mbar_wait(bar_full + (item - DEPTH) * 8);
            const uint32_t fb = bar_full + item * 8;
            if (lane == 0) mbar_expect_tx(fb, bytes);
            __syncwarp();
            if (wi < 2) {
                if (lane < 16) bulk_load(sbase + dst + lane * WPITCH, wo + (size_t)(32 * j + wi * 16 + lane) * kD, 1152, fb, pol);
            } else if (wi < 10) {
                if (lane == 0) tma2d(sbase + dst, ((wi - 2) & 1) ? &tm_w3 : &tm_w1, c0, ((wi - 2) >> 1) * 144, fb);
            } else {
                const int q = wi - 10;
                if (lane < (q < 2 ? 16 : 4)) bulk_load(sbase + dst + lane * WPITCH, w2 + (size_t)(36 * j + q * 16 + lane) * kD, 1152, fb, pol);
            }
        }
        TS(9);
        return;
    }

    float* s_act = reinterpret_cast<float*>(smem + SM_U);
    float* s_ln  = s_act + 2 * kD;
    float* s_mrg = reinterpret_cast<float*>(smem + SM_U);
    float* s_x1  = reinterpret_cast<float*>(smem + SM_U);
    bf16*  s_h2  = reinterpret_cast<bf16*>(smem + SM_U + 4608);
    float* s_cb1 = reinterpret_cast<float*>(smem + SM_CB1);
    float* s_sb  = reinterpret_cast<float*>(smem + SM_SB);
    float* s_red = reinterpret_cast<float*>(smem + SM_RED);
    uint32_t* s_qs = reinterpret_cast<uint32_t*>(smem + SM_QS);
    float* s_ml  = reinterpret_cast<float*>(smem + SM_ML);
    bf16*  s_os  = reinterpret_cast<bf16*>(smem + SM_OS);
    bf16*  s_hh  = reinterpret_cast<bf16*>(smem + SM_HH);
    float* s_own = reinterpret_cast<float*>(smem + SM_OWN);
    unsigned* s_tag = reinterpret_cast<unsigned*>(smem + SM_TAG);

    if (warp == 0) TS(0);
    uint4 wm[9], wqr[9];
    {
        const int rg = tid >> 2, co = tid & 3;
        if (j < 108) {
#pragma unroll
            for (int i = 0; i < 9; i++) wm[i] = ldg_nc(wmod + (size_t)(rg + 64 * i) * kMOD + 32 * j + 8 * co);
        }
#pragma unroll
        for (int i = 0; i < 9; i++) wqr[i] = ldg_nc(wq + (size_t)(rg + 64 * i) * kQD + 32 * j + 8 * co);
    }
    if (tid < 144) {
        const uint4 cv = *reinterpret_cast<const uint4*>(cvec + tid * 8);
        const uint4 xv = *reinterpret_cast<const uint4*>(x + tid * 8);
        const uint32_t cc[4] = {cv.x, cv.y, cv.z, cv.w}, xx[4] = {xv.x, xv.y, xv.z, xv.w};
#pragma unroll
        for (int k = 0; k < 4; k++) {
            s_act[tid * 8 + 2 * k] = bfr(silu_f(bf_lo(cc[k])));
            s_act[tid * 8 + 2 * k + 1] = bfr(silu_f(bf_hi(cc[k])));
            s_ln[tid * 8 + 2 * k] = bf_lo(xx[k]);
            s_ln[tid * 8 + 2 * k + 1] = bf_hi(xx[k]);
        }
    } else if (tid == 160) {
        const unsigned n = ld_rlx1(&g_arrive) >> 10;
        s_tag[0] = n + 1;
        s_tag[1] = (n + 1) << 10;
    }
    __syncthreads();
    const unsigned tag = s_tag[0];
    float xv8[8];
    {
        float m0, sd0, m1, sd1;
        ln_stats(s_ln, lane, m0, sd0);
        ln_stats(s_ln + kD, lane, m1, sd1);
        if (tid < 144) {
            const float m = tid < 72 ? m0 : m1, sd = tid < 72 ? sd0 : sd1;
#pragma unroll
            for (int k = 0; k < 8; k++) xv8[k] = bfr(bfr(s_ln[tid * 8 + k] - m) / sd);
        }
        if (j < NOWN && tid >= 160 && tid < 176) s_own[tid - 160] = s_ln[(j / 36) * kD + (j % 36) * 16 + tid - 160];
    }
    if (j < 108) {
        gemv_regs(wm, s_act, s_red, tid);
        cons_bar();
        if (tid < 32) {
            float a = 0.f, b = 0.f;
#pragma unroll
            for (int w = 0; w < 8; w++) { const float2 v = *reinterpret_cast<const float2*>(s_red + w * 64 + tid * 2); a += v.x; b += v.y; }
            st_rlx_unit(&g_mod[(tid >> 4) * (kMOD / 2) + 16 * j + (tid & 15)], pack_bf(a, b), tag);
        }
    }
    if (warp == 0) TS(1);
    {
        float hv[8];
        if (tid < 144) {
            const int b = tid / 72, n0 = (tid % 72) * 8;
            const uint2* psa = g_mod + b * (kMOD / 2) + n0 / 2;
            const uint2* pca = psa + kD / 2;
            uint4 s0, s1, c0, c1;
            int spin = 0;
            while (true) {
                s0 = ld_rlx_units2(psa); s1 = ld_rlx_units2(psa + 2);
                c0 = ld_rlx_units2(pca); c1 = ld_rlx_units2(pca + 2);
                if (s0.y == tag && s0.w == tag && s1.y == tag && s1.w == tag && c0.y == tag && c0.w == tag && c1.y == tag && c1.w == tag) break;
                if (++spin > SPIN_LIMIT) __trap();
            }
            const uint32_t ss[4] = {s0.x, s0.z, s1.x, s1.z}, cc[4] = {c0.x, c0.z, c1.x, c1.z};
#pragma unroll
            for (int k = 0; k < 4; k++) {
                hv[2 * k] = bfr(bfr(xv8[2 * k] * bfr(1.0f + bf_lo(cc[k]))) + bf_lo(ss[k]));
                hv[2 * k + 1] = bfr(bfr(xv8[2 * k + 1] * bfr(1.0f + bf_hi(cc[k]))) + bf_hi(ss[k]));
            }
        }
        cons_bar();
        if (tid < 144) {
            *reinterpret_cast<float4*>(s_act + tid * 8) = make_float4(hv[0], hv[1], hv[2], hv[3]);
            *reinterpret_cast<float4*>(s_act + tid * 8 + 4) = make_float4(hv[4], hv[5], hv[6], hv[7]);
        }
        cons_bar();
    }
    if (warp == 0) TS(2);
    gemv_regs(wqr, s_act, s_red, tid);
    cons_bar();
    if (tid < 32) {
        float a = 0.f, b = 0.f;
#pragma unroll
        for (int w = 0; w < 8; w++) { const float2 v = *reinterpret_cast<const float2*>(s_red + w * 64 + tid * 2); a += v.x; b += v.y; }
        st_rlx_unit(&g_q[(tid >> 4) * (kQD / 2) + 16 * j + (tid & 15)], pack_bf(a, b), tag);
    }
    if (tid >= 64 && tid < 128) {
        const uint2* p = g_q + bb * (kQD / 2) + grp * 128 + (tid - 64) * 2;
        uint4 v;
        int spin = 0;
        while (true) {
            v = ld_rlx_units2(p);
            if (v.y == tag && v.w == tag) break;
            if (++spin > SPIN_LIMIT) __trap();
        }
        *reinterpret_cast<uint2*>(s_qs + (tid - 64) * 2) = make_uint2(v.x, v.z);
    }
    cons_bar();
    if (warp == 0) TS(3);

    const int g = lane >> 2, t = lane & 3;
    const int np = g >> 1;
    uint32_t qf[16];
#pragma unroll
    for (int c = 0; c < 16; c++) qf[c] = s_qs[(g & 1) * 64 + 4 * (c ^ np) + t];
    const bool is_lo = (t == (g >> 2)), is_hi = (t == 2 + (g >> 2));
    const int e = np & 1;
    const uint32_t mlo = is_lo ? 0xFFFFFFFFu : 0u, mhi = is_hi ? 0xFFFFFFFFu : 0u;
    const int src_lo = 4 * g + (g >> 2), src_hi = src_lo + 2;
    const int r8 = lane & 7, mi = lane >> 3;
    const uint32_t koff0 = r8 * 256 + ((mi ^ r8) << 4), koff1 = r8 * 256 + (((mi | 4) ^ r8) << 4);
    uint32_t voff[4];
#pragma unroll
    for (int c = 0; c < 4; c++) voff[c] = ((mi & 1) * 8 + r8) * 256 + (((2 * c + (mi >> 1)) ^ r8) << 4);
    const float kScale = 0.08838834764831845f, kLog2e = 1.4426950408889634f;

    float O[16][4];
#pragma unroll
    for (int c = 0; c < 16; c++) { O[c][0] = O[c][1] = O[c][2] = O[c][3] = 0.f; }
    float m_run = -INFINITY, l_run = 0.f;

#pragma unroll 1
    for (int it = 0; it < 4; it++) {
        const int iK = 2 * (warp + 8 * it), iV = iK + 1;
        const uint32_t kb = sbase + phys_slot(iK) * SLOT, vb = sbase + phys_slot(iV) * SLOT;
        float S[8][4];
#pragma unroll
        for (int n = 0; n < 8; n++) { S[n][0] = S[n][1] = S[n][2] = S[n][3] = 0.f; }
        mbar_wait(bar_full + iK * 8);
#pragma unroll
        for (int s2 = 0; s2 < 4; s2++) {
            const uint32_t a = kb + ((s2 & 1) ? koff1 : koff0) + (s2 >> 1) * 128;
#pragma unroll
            for (int n = 0; n < 8; n++) {
                uint32_t b0, b1, b2, b3;
                ldsm4(a + n * 2048, b0, b1, b2, b3);
                mma16816(S[n], qf[4 * s2], qf[(4 * s2) ^ 4], qf[4 * s2 + 1], qf[(4 * s2 + 1) ^ 4], b0, b1);
                mma16816(S[n], qf[4 * s2 + 2], qf[(4 * s2 + 2) ^ 4], qf[4 * s2 + 3], qf[(4 * s2 + 3) ^ 4], b2, b3);
            }
        }
        __syncwarp();
        if (lane == 0) mbar_arrive(bar_empty + iK * 8);
        float sc[8];
        float mx = m_run;
#pragma unroll
        for (int n = 0; n < 8; n++) {
            const float a = e ? S[n][1] : S[n][0], b = e ? S[n][3] : S[n][2];
            sc[n] = bfr(bfr(is_lo ? a : b) * kScale);
            mx = fmaxf(mx, sc[n]);
        }
        const float corr = ex2((m_run - mx) * kLog2e);
        m_run = mx;
        uint32_t pk[8];
        float ps = 0.f;
#pragma unroll
        for (int n = 0; n < 8; n++) {
            const float p = ex2((sc[n] - mx) * kLog2e);
            ps += p;
            pk[n] = e ? pack_bf(0.f, p) : pack_bf(p, 0.f);
        }
        l_run = l_run * corr + ps;
        const float c_lo = __shfl_sync(0xffffffffu, corr, src_lo), c_hi = __shfl_sync(0xffffffffu, corr, src_hi);
        if (__any_sync(0xffffffffu, c_lo != 1.0f || c_hi != 1.0f)) {
#pragma unroll
            for (int c = 0; c < 16; c++) { O[c][0] *= c_lo; O[c][1] *= c_lo; O[c][2] *= c_hi; O[c][3] *= c_hi; }
        }
        mbar_wait(bar_full + iV * 8);
#pragma unroll
        for (int u = 0; u < 4; u++) {
            const uint32_t a0 = pk[2 * u] & mlo, a1 = pk[2 * u] & mhi, a2 = pk[2 * u + 1] & mlo, a3 = pk[2 * u + 1] & mhi;
#pragma unroll
            for (int cp = 0; cp < 8; cp++) {
                uint32_t b0, b1, b2, b3;
                ldsm4t(vb + voff[cp & 3] + u * 4096 + (cp >> 2) * 128, b0, b1, b2, b3);
                mma16816(O[2 * cp], a0, a1, a2, a3, b0, b1);
                mma16816(O[2 * cp + 1], a0, a1, a2, a3, b2, b3);
            }
        }
        __syncwarp();
        if (lane == 0) mbar_arrive(bar_empty + iV * 8);

        if (it == 0) {
            if (tid < 144) {
                const int b = tid / 72, n0 = (tid % 72) * 8;
                const uint2* psb = g_mod + b * (kMOD / 2) + (3 * kD + n0) / 2;
                const uint2* pcb = psb + kD / 2;
                uint4 s0, s1, c0, c1;
                int spin = 0;
                while (true) {
                    s0 = ld_rlx_units2(psb); s1 = ld_rlx_units2(psb + 2);
                    c0 = ld_rlx_units2(pcb); c1 = ld_rlx_units2(pcb + 2);
                    if (s0.y == tag && s0.w == tag && s1.y == tag && s1.w == tag && c0.y == tag && c0.w == tag && c1.y == tag && c1.w == tag) break;
                    if (++spin > SPIN_LIMIT) __trap();
                }
                const uint32_t ss[4] = {s0.x, s0.z, s1.x, s1.z}, cc[4] = {c0.x, c0.z, c1.x, c1.z};
#pragma unroll
                for (int k = 0; k < 4; k++) {
                    s_cb1[tid * 8 + 2 * k] = bfr(1.0f + bf_lo(cc[k]));
                    s_cb1[tid * 8 + 2 * k + 1] = bfr(1.0f + bf_hi(cc[k]));
                    s_sb[tid * 8 + 2 * k] = bf_lo(ss[k]);
                    s_sb[tid * 8 + 2 * k + 1] = bf_hi(ss[k]);
                }
            } else if (j < NOWN && tid >= 160 && tid < 176) {
                const int k = tid - 160, which = k >> 3;
                const uint2* p = g_mod + (j / 36) * (kMOD / 2) + ((which ? 5 : 2) * kD + (j % 36) * 16) / 2 + (k & 7);
                uint2 v;
                int spin = 0;
                while (true) {
                    unsigned long long u;
                    asm volatile("ld.relaxed.gpu.global.u64 %0, [%1];" : "=l"(u) : "l"(p) : "memory");
                    v = make_uint2((uint32_t)u, (uint32_t)(u >> 32));
                    if (v.y == tag) break;
                    if (++spin > SPIN_LIMIT) __trap();
                }
                s_own[16 + which * 16 + (k & 7) * 2] = bf_lo(v.x);
                s_own[16 + which * 16 + (k & 7) * 2 + 1] = bf_hi(v.x);
            }
            __syncwarp();
        } else if (it == 1) {
            const uint4 ev = make_uint4(EMPTY, EMPTY, EMPTY, EMPTY);
            if (lane < 9) st_rlx4(g_x3 + (j * 8 + warp) * 36 + lane * 4, ev);
            if (j < NOWN) {
                st_rlx4(g_x4 + j * (NCTA * 16) + tid * 4, ev);
                st_rlx4(g_x4 + j * (NCTA * 16) + 1024 + tid * 4, ev);
                st_rlx4(g_x6 + j * (NCTA * 16) + tid * 4, ev);
                st_rlx4(g_x6 + j * (NCTA * 16) + 1024 + tid * 4, ev);
                if (tid < 2) st_rlx4(g_x5 + j * 8 + tid * 4, ev);
            }
            __syncwarp();
            if (lane == 0) {
                __threadfence();
                asm volatile("red.release.gpu.global.add.u32 [%0], 1;" ::"l"(&g_arrive) : "memory");
            }
        }
    }
    if (warp == 7) TS(4);

    {
        const float m_lo = __shfl_sync(0xffffffffu, m_run, src_lo), m_hi = __shfl_sync(0xffffffffu, m_run, src_hi);
        const float l_lo = __shfl_sync(0xffffffffu, l_run, src_lo), l_hi = __shfl_sync(0xffffffffu, l_run, src_hi);
        float M = fmaxf(m_lo, m_hi);
        M = fmaxf(M, __shfl_xor_sync(0xffffffffu, M, 8));
        M = fmaxf(M, __shfl_xor_sync(0xffffffffu, M, 16));
        const float f_lo = ex2((m_lo - M) * kLog2e), f_hi = ex2((m_hi - M) * kLog2e);
        float L = l_lo * f_lo + l_hi * f_hi;
        L += __shfl_xor_sync(0xffffffffu, L, 8);
        L += __shfl_xor_sync(0xffffffffu, L, 16);
        float Om[16][2];
#pragma unroll
        for (int c = 0; c < 16; c++) {
            Om[c][0] = O[c][0] * f_lo + O[c ^ 4][2] * f_hi;
            Om[c][1] = O[c][1] * f_lo + O[c ^ 4][3] * f_hi;
        }
#pragma unroll
        for (int c = 0; c < 16; c += 2) {
            Om[c][0] += __shfl_xor_sync(0xffffffffu, Om[c ^ 1][0], 8);
            Om[c][1] += __shfl_xor_sync(0xffffffffu, Om[c ^ 1][1], 8);
        }
#pragma unroll
        for (int c = 0; c < 16; c += 4) {
            Om[c][0] += __shfl_xor_sync(0xffffffffu, Om[c ^ 2][0], 16);
            Om[c][1] += __shfl_xor_sync(0xffffffffu, Om[c ^ 2][1], 16);
            *reinterpret_cast<float2*>(s_mrg + (warp * 2 + (g & 1)) * 128 + 8 * (c ^ np) + 2 * t) = make_float2(Om[c][0], Om[c][1]);
        }
        if (lane == 0 || lane == 4) { s_ml[(warp * 2 + g) * 2] = M; s_ml[(warp * 2 + g) * 2 + 1] = L; }
        if (tid == 0) {
            const unsigned target = s_tag[1];
            int spin = 0;
            while ((int)(ld_acq1(&g_arrive) - target) < 0) { if (++spin > SPIN_LIMIT) __trap(); }
        }
    }
    cons_bar();
    {
        const int h = tid >> 7, d = tid & 127;
        float mw[8], M = -INFINITY;
#pragma unroll
        for (int w = 0; w < 8; w++) { mw[w] = s_ml[(w * 2 + h) * 2]; M = fmaxf(M, mw[w]); }
        float o = 0.f, L = 0.f;
#pragma unroll
        for (int w = 0; w < 8; w++) {
            const float f = ex2((mw[w] - M) * kLog2e);
            o = fmaf(f, s_mrg[(w * 2 + h) * 128 + d], o);
            L = fmaf(f, s_ml[(w * 2 + h) * 2 + 1], L);
        }
        float* dst = g_x3 + ((grp * 8 + h * 4 + (d >> 5)) * 8 + rnk) * 36;
        st_rlx1(dst + (d & 31), canon(o));
        if ((d & 31) == 0) st_rlx2(dst + 32, canon(M), canon(L));
    }
    if (tid < 64) {
        const int b = tid >> 5, i = tid & 31;
        const float* p = g_x3 + (j * 8 + b * 4) * 36;
        unsigned ov[4];
        uint2 ml[4];
        int spin = 0;
        while (true) {
            bool ok = true;
#pragma unroll
            for (int s = 0; s < 4; s++) { ov[s] = ld_rlx1(p + s * 36 + i); ml[s] = ld_rlx2(p + s * 36 + 32); }
#pragma unroll
            for (int s = 0; s < 4; s++) ok = ok && ov[s] != EMPTY && ml[s].x != EMPTY && ml[s].y != EMPTY;
            if (ok) break;
            if (++spin > SPIN_LIMIT) __trap();
        }
        float M = -INFINITY;
#pragma unroll
        for (int s = 0; s < 4; s++) M = fmaxf(M, __uint_as_float(ml[s].x));
        float o = 0.f, L = 0.f;
#pragma unroll
        for (int s = 0; s < 4; s++) {
            const float f = ex2((__uint_as_float(ml[s].x) - M) * kLog2e);
            o = fmaf(f, __uint_as_float(ov[s]), o);
            L = fmaf(f, __uint_as_float(ml[s].y), L);
        }
        s_os[b * 32 + i] = __float2bfloat16_rn(o / L);
    }
    cons_bar();
    if (warp == 0) TS(5);
    {
        uint32_t a[4] = {0u, 0u, 0u, 0u};
        if (g < 2) {
            const uint32_t* p = reinterpret_cast<const uint32_t*>(s_os) + g * 16 + t;
            a[0] = p[0]; a[1] = p[4]; a[2] = p[8]; a[3] = p[12];
        }
        mbar_wait(bar_full + (NKV + 0) * 8);
        mbar_wait(bar_full + (NKV + 1) * 8);
        const uint32_t base = sbase + OFF_WO + lane * WPITCH + warp * 9 * 16;
#pragma unroll
        for (int n = 0; n < 9; n++) {
            uint32_t b0, b1, b2, b3;
            float c[4] = {0.f, 0.f, 0.f, 0.f};
            ldsm4t(base + n * 16, b0, b1, b2, b3);
            mma16816(c, a[0], 0u, a[1], 0u, b0, b1);
            mma16816(c, a[2], 0u, a[3], 0u, b2, b3);
            const int nt = warp * 9 + n;
            if (g < 2) st_rlx2(g_x4 + ((g * 36 + (nt >> 1)) * NCTA + j) * 16 + (nt & 1) * 8 + 2 * t, canon(c[0]), canon(c[1]));
        }
    }
    if (j < NOWN) {
        const float s = owner_reduce(g_x4 + j * (NCTA * 16), s_red, tid);
        if (warp == 0) {
            float x1 = 0.f;
            if (tid < 16) {
                x1 = bfr(s_own[tid] + bfr(s_own[16 + tid] * bfr(s)));
                s_own[48 + tid] = x1;
            }
            const float nb = __shfl_down_sync(0xffffffffu, x1, 1);
            if (tid < 16 && !(tid & 1)) {
                uint32_t u = pack_bf(x1, nb);
                if (u == EMPTY) u = 0x7FFF7FFFu;
                st_rlx1(g_x5 + j * 8 + (tid >> 1), u);
            }
        }
    }
    if (warp == 0) TS(6);
    if (tid < 144) {
        uint4 v;
        int spin = 0;
        while (true) {
            v = ld_rlx4(g_x5 + tid * 4);
            if (v.x != EMPTY && v.y != EMPTY && v.z != EMPTY && v.w != EMPTY) break;
            if (++spin > SPIN_LIMIT) __trap();
        }
        *reinterpret_cast<float4*>(s_x1 + tid * 8) = make_float4(bf_lo(v.x), bf_hi(v.x), bf_lo(v.y), bf_hi(v.y));
        *reinterpret_cast<float4*>(s_x1 + tid * 8 + 4) = make_float4(bf_lo(v.z), bf_hi(v.z), bf_lo(v.w), bf_hi(v.w));
    } else if (tid >= 160 && tid < 172) {
        reinterpret_cast<uint32_t*>(s_hh)[(tid - 160) / 6 * 24 + 18 + (tid - 160) % 6] = 0u;
    }
    cons_bar();
    if (warp == 0) TS(7);
    {
        const int kq = warp & 3, mat = warp >> 2;
        float m0, sd0, m1, sd1;
        ln_stats(s_x1, lane, m0, sd0);
        ln_stats(s_x1 + kD, lane, m1, sd1);
#pragma unroll
        for (int i = 0; i < 9; i++) {
            const int idx = lane + 32 * i, b = idx >= 144;
            const int n = b * kD + kq * 144 + (idx - b * 144);
            const float ln = bfr(bfr(s_x1[n] - (b ? m1 : m0)) / (b ? sd1 : sd0));
            s_h2[n] = __float2bfloat16_rn(bfr(ln * s_cb1[n]) + s_sb[n]);
        }
        __syncwarp();
        float c[5][4];
#pragma unroll
        for (int n = 0; n < 5; n++) { c[n][0] = c[n][1] = c[n][2] = c[n][3] = 0.f; }
        const uint32_t* ph = reinterpret_cast<const uint32_t*>(s_h2) + (g & 1) * (kD / 2) + kq * 72 + t;
        const uint32_t am = g < 2 ? 0xFFFFFFFFu : 0u;
        mbar_wait(bar_full + (NKV + 2 + kq * 2 + mat) * 8);
        const uint32_t base = sbase + (mat ? OFF_W3 : OFF_W1) + (kq * 144 + (mi & 1) * 8 + r8) * 80 + (mi >> 1) * 16;
#pragma unroll
        for (int s = 0; s < 9; s++) {
            const uint32_t a0 = ph[s * 8] & am, a2 = ph[s * 8 + 4] & am;
            uint32_t b0, b1, b2, b3;
            ldsm4t(base + s * 1280, b0, b1, b2, b3);
            mma16816(c[0], a0, 0u, a2, 0u, b0, b1);
            mma16816(c[1], a0, 0u, a2, 0u, b2, b3);
            ldsm4t(base + s * 1280 + 32, b0, b1, b2, b3);
            mma16816(c[2], a0, 0u, a2, 0u, b0, b1);
            mma16816(c[3], a0, 0u, a2, 0u, b2, b3);
            ldsm2t(base - (mi >> 1) * 16 + s * 1280 + 64, b0, b1);
            mma16816(c[4], a0, 0u, a2, 0u, b0, b1);
        }
        if (g < 2) {
#pragma unroll
            for (int n = 0; n < 5; n++)
                *reinterpret_cast<float2*>(s_red + (warp * 2 + g) * 40 + n * 8 + 2 * t) = make_float2(c[n][0], c[n][1]);
        }
    }
    cons_bar();
    if (tid < 72) {
        const int b = tid / 36, i = tid % 36, col = (j & 1) * 4 + i;
        float ga = 0.f, up = 0.f;
#pragma unroll
        for (int q = 0; q < 4; q++) { ga += s_red[(q * 2 + b) * 40 + col]; up += s_red[((4 + q) * 2 + b) * 40 + col]; }
        ga = bfr(ga); up = bfr(up);
        s_hh[b * 48 + i] = __float2bfloat16_rn(bfr(silu_f(ga)) * up);
    }
    cons_bar();
    if (warp == 0) TS(10);
    {
        uint32_t a[6] = {0u, 0u, 0u, 0u, 0u, 0u};
        if (g < 2) {
            const uint32_t* p = reinterpret_cast<const uint32_t*>(s_hh) + g * 24 + t;
#pragma unroll
            for (int k = 0; k < 6; k++) a[k] = p[4 * k];
        }
        float c[9][4];
        mbar_wait(bar_full + (NKV + 10) * 8);
        mbar_wait(bar_full + (NKV + 11) * 8);
        const uint32_t base = sbase + OFF_W2 + lane * WPITCH + warp * 9 * 16;
#pragma unroll
        for (int n = 0; n < 9; n++) {
            uint32_t b0, b1, b2, b3;
            c[n][0] = c[n][1] = c[n][2] = c[n][3] = 0.f;
            ldsm4t(base + n * 16, b0, b1, b2, b3);
            mma16816(c[n], a[0], 0u, a[1], 0u, b0, b1);
            mma16816(c[n], a[2], 0u, a[3], 0u, b2, b3);
        }
        mbar_wait(bar_full + (NKV + 12) * 8);
        const uint32_t base2 = sbase + OFF_W2 + min(32 + (lane & 15), 35) * WPITCH + warp * 9 * 16;
#pragma unroll
        for (int n = 0; n < 9; n++) {
            uint32_t b0, b1;
            ldsm2t(base2 + n * 16, b0, b1);
            mma16816(c[n], a[4], 0u, a[5], 0u, b0, b1);
            const int nt = warp * 9 + n;
            if (g < 2) st_rlx2(g_x6 + ((g * 36 + (nt >> 1)) * NCTA + j) * 16 + (nt & 1) * 8 + 2 * t, canon(c[n][0]), canon(c[n][1]));
        }
    }
    if (warp == 0) TS(11);
    if (j < NOWN) {
        const float s = owner_reduce(g_x6 + j * (NCTA * 16), s_red, tid);
        if (tid < 16) out[(j / 36) * kD + (j % 36) * 16 + tid] = __float2bfloat16_rn(s_own[48 + tid] + bfr(s_own[32 + tid] * bfr(s)));
        if (warp == 0) TS(12);
    }
}

typedef CUresult (*EncodeTiledFn)(CUtensorMap*, CUtensorMapDataType, cuuint32_t, void*, const cuuint64_t*, const cuuint64_t*,
                                  const cuuint32_t*, const cuuint32_t*, CUtensorMapInterleave, CUtensorMapSwizzle,
                                  CUtensorMapL2promotion, CUtensorMapFloatOOBfill);

}

extern "C" void kernel_launch(void* const* d_in, const int* in_sizes, int n_in, void* d_out, int out_size) {
    (void)in_sizes; (void)n_in; (void)out_size;
    static EncodeTiledFn enc = nullptr;
    if (!enc) {
        void* fn = nullptr;
        cudaDriverEntryPointQueryResult qr;
        cudaGetDriverEntryPoint("cuTensorMapEncodeTiled", &fn, cudaEnableDefault, &qr);
        enc = (EncodeTiledFn)fn;
        cudaFuncSetAttribute(fused_kernel, cudaFuncAttributeMaxDynamicSharedMemorySize, SM_TOTAL);
    }
    const bf16* x    = (const bf16*)d_in[0];
    const bf16* kc   = (const bf16*)d_in[1];
    const bf16* vc   = (const bf16*)d_in[2];
    const bf16* wq   = (const bf16*)d_in[3];
    const bf16* wo   = (const bf16*)d_in[4];
    void* w1         = d_in[6];
    void* w3         = d_in[7];
    const bf16* w2   = (const bf16*)d_in[8];
    const bf16* cvec = (const bf16*)d_in[9];
    const bf16* wmod = (const bf16*)d_in[10];

    CUtensorMap tm1, tm3;
    const cuuint64_t dims[2] = {(cuuint64_t)kF, (cuuint64_t)kD};
    const cuuint64_t strides[1] = {(cuuint64_t)kF * 2};
    const cuuint32_t box[2] = {40, 144};
    const cuuint32_t es[2] = {1, 1};
    enc(&tm1, CU_TENSOR_MAP_DATA_TYPE_BFLOAT16, 2, w1, dims, strides, box, es, CU_TENSOR_MAP_INTERLEAVE_NONE,
        CU_TENSOR_MAP_SWIZZLE_NONE, CU_TENSOR_MAP_L2_PROMOTION_L2_128B, CU_TENSOR_MAP_FLOAT_OOB_FILL_NONE);
    enc(&tm3, CU_TENSOR_MAP_DATA_TYPE_BFLOAT16, 2, w3, dims, strides, box, es, CU_TENSOR_MAP_INTERLEAVE_NONE,
        CU_TENSOR_MAP_SWIZZLE_NONE, CU_TENSOR_MAP_L2_PROMOTION_L2_128B, CU_TENSOR_MAP_FLOAT_OOB_FILL_NONE);

    fused_kernel<<<NCTA, NTHR, SM_TOTAL>>>(tm1, tm3, x, kc, vc, wq, wo, w2, cvec, wmod, (bf16*)d_out);
}
```

```cpp
#include <cuda_runtime.h>
#include <cuda_bf16.h>
#include <cuda.h>
#include <stdint.h>

namespace {

typedef __nv_bfloat16 bf16;

constexpr int kD    = 576;
constexpr int kF    = 4608;
constexpr int kQD   = 4096;
constexpr int kMOD  = 6 * kD;
constexpr int kSK   = 8192;
constexpr int NCTA  = 128;
constexpr int NTHR  = 384;
constexpr int SLOT  = 16384;
constexpr int NS    = 11;
constexpr int NKV   = 64;
constexpr int NW    = 8;
constexpr int NITEM = NKV + NW;
constexpr int DHEAD = 3;
constexpr int DEPTH = 3, DMIN = 2, DMAX = 5;
constexpr int LAG   = 2;
constexpr int WOD   = 3;
constexpr int WDEPTH = 2, WMIN = 2, WMAX = 3;
constexpr int MONNS = 300;
constexpr int PFCLK = 1150;
constexpr int NOWN  = 72;

__host__ __device__ constexpr int ring_off(int pos) { return ((pos + NS - (NKV - 2) % NS) % NS) * SLOT; }
__host__ __device__ constexpr int item_off(int i) { return i < NS ? ring_off(i) : (i < NS + 2 ? NS * SLOT + (i - NS) * SLOT : ring_off(i - 2)); }
__host__ __device__ constexpr int prev_user(int i) { return i - 2 - NS < NS ? i - 2 - NS : i - NS; }
constexpr int BOXB   = 72 * 128;
constexpr int QB     = 72 * 288;
constexpr int OFF_W1 = 0, OFF_W3 = 2 * QB;
constexpr int OFF_W2 = 4 * QB;
static_assert(OFF_W2 + 2 * QB <= NS * SLOT && QB % 128 == 0, "tail weights");
constexpr int CPITCH = 176;
constexpr int OFF_WQ = NS * SLOT;
constexpr int OFF_WC = item_off(NS - 1);
constexpr int OFF_WM = NS * SLOT;
constexpr int OFF_WO = NS * SLOT;

constexpr int SM_BAR  = OFF_WQ + 4 * BOXB;
constexpr int SM_MRG  = SM_BAR + 1280;
constexpr int SM_QS   = SM_MRG + 1280;
constexpr int SM_HH   = SM_QS + 512;
constexpr int SM_X1   = SM_HH + 576;
constexpr int SM_AVG  = SM_X1 + 2304;
constexpr int SM_TOTAL = SM_AVG + 64;
static_assert(SM_TOTAL <= 232448, "smem");
constexpr int BAR_CRIT = SM_BAR, BAR_WQ = SM_BAR + 8, BAR_FULL = SM_BAR + 24, BAR_EMPTY = BAR_FULL + NITEM * 8,
              BAR_CHAIN = BAR_EMPTY + NKV * 8, BAR_WM = BAR_CHAIN + 64, BAR_WMDONE = BAR_WM + 8, BAR_GATE = BAR_WMDONE + 8,
              BAR_SENT = BAR_GATE + 8;
constexpr int NBAR = NITEM + NKV + 8 + 4;
constexpr int NPINIT = 6;
static_assert((NBAR + 3) * 8 <= 1280, "barrier region");

constexpr unsigned EMPTY = 0xFFFFFFFFu;
constexpr unsigned FULLM = 0xFFFFFFFFu;
constexpr int SPIN_LIMIT = 1 << 22;
constexpr float kScale = 0.08838834764831845f, kLog2e = 1.4426950408889634f;

__device__ unsigned g_arrive;
__device__ unsigned g_prog;
__device__ __align__(128) uint2 g_mod[2 * (kMOD / 2)];
__device__ __align__(128) uint2 g_mc[16 * 8 * 2 * 72];
__device__ __align__(128) uint2 g_qp[16 * 8 * 2 * 256];
__device__ __align__(128) float g_x3[NCTA * 2 * 132];
__device__ __align__(128) float g_xr[2][2 * 72 * 32 * 8];
__device__ __align__(128) unsigned g_x5[8 * kD];
__device__ __align__(128) float g_x7[NCTA * 576];
#define TS(i) do {} while (0)

__device__ __forceinline__ void mbar_init(uint32_t bar, uint32_t cnt) {
    asm volatile("mbarrier.init.shared::cta.b64 [%0], %1;" ::"r"(bar), "r"(cnt) : "memory");
}
__device__ __forceinline__ void mbar_expect_tx(uint32_t bar, uint32_t bytes) {
    asm volatile("mbarrier.arrive.expect_tx.shared::cta.b64 _, [%0], %1;" ::"r"(bar), "r"(bytes) : "memory");
}
__device__ __forceinline__ void mbar_arrive(uint32_t bar) {
    asm volatile("mbarrier.arrive.shared::cta.b64 _, [%0];" ::"r"(bar) : "memory");
}
__device__ __forceinline__ uint32_t mbar_try(uint32_t bar) {
    uint32_t ok;
    asm volatile("{\n.reg .pred p;\nmbarrier.try_wait.parity.shared::cta.b64 p, [%1], 0;\nselp.u32 %0, 1, 0, p;\n}"
                 : "=r"(ok) : "r"(bar) : "memory");
    return ok;
}
__device__ __forceinline__ uint32_t mbar_test(uint32_t bar) {
    uint32_t ok;
    asm volatile("{\n.reg .pred p;\nmbarrier.test_wait.parity.shared::cta.b64 p, [%1], 0;\nselp.u32 %0, 1, 0, p;\n}"
                 : "=r"(ok) : "r"(bar) : "memory");
    return ok;
}
__device__ __forceinline__ void mbar_wait1(uint32_t bar) {
    if (mbar_try(bar)) return;
    const long long t0 = clock64();
    while (!mbar_try(bar)) { if (clock64() - t0 > (4ll << 30)) __trap(); }
}
__device__ __forceinline__ void mbar_wait(uint32_t bar) {
    if (__all_sync(FULLM, mbar_try(bar))) return;
    const long long t0 = clock64();
    while (!__all_sync(FULLM, mbar_try(bar))) { if (clock64() - t0 > (4ll << 30)) __trap(); }
}
__device__ __forceinline__ void bulk_load(uint32_t dst, const void* src, uint32_t bytes, uint32_t bar, uint64_t pol) {
    asm volatile("cp.async.bulk.shared::cluster.global.mbarrier::complete_tx::bytes.L2::cache_hint [%0], [%1], %2, [%3], %4;"
                 ::"r"(dst), "l"(src), "r"(bytes), "r"(bar), "l"(pol) : "memory");
}
__device__ __forceinline__ void tma2d(uint32_t dst, const CUtensorMap* tm, int c0, int c1, uint32_t bar) {
    asm volatile("cp.async.bulk.tensor.2d.shared::cluster.global.mbarrier::complete_tx::bytes [%0], [%1, {%3, %4}], [%2];"
                 ::"r"(dst), "l"(tm), "r"(bar), "r"(c0), "r"(c1) : "memory");
}
__device__ __forceinline__ void cp16(uint32_t dst, const void* src) {
    asm volatile("cp.async.cg.shared.global [%0], [%1], 16;" ::"r"(dst), "l"(src) : "memory");
}
__device__ __forceinline__ void cp_commit() { asm volatile("cp.async.commit_group;" ::: "memory"); }
template <int N> __device__ __forceinline__ void cp_wait() { asm volatile("cp.async.wait_group %0;" ::"n"(N) : "memory"); }
__device__ __forceinline__ void cons_bar() { asm volatile("bar.sync 1, 256;" ::: "memory"); }

__device__ __forceinline__ unsigned ld_rlx1(const void* p) {
    unsigned v;
    asm volatile("ld.relaxed.gpu.global.u32 %0, [%1];" : "=r"(v) : "l"(p) : "memory");
    return v;
}
__device__ __forceinline__ void repoll4(uint4& v, const void* p) {
    asm volatile("{\n.reg .pred q;\n.reg .u32 m;\nmax.u32 m, %0, %1;\nmax.u32 m, m, %2;\nmax.u32 m, m, %3;\nsetp.eq.u32 q, m, 0xFFFFFFFF;\n"
                 "@q ld.relaxed.gpu.global.v4.u32 {%0,%1,%2,%3}, [%4];\n}"
                 : "+r"(v.x), "+r"(v.y), "+r"(v.z), "+r"(v.w) : "l"(p) : "memory");
}
__device__ __forceinline__ void repoll2(uint2& v, const void* p) {
    asm volatile("{\n.reg .pred q;\n.reg .u32 m;\nmax.u32 m, %0, %1;\nsetp.eq.u32 q, m, 0xFFFFFFFF;\n"
                 "@q ld.relaxed.gpu.global.v2.u32 {%0,%1}, [%2];\n}"
                 : "+r"(v.x), "+r"(v.y) : "l"(p) : "memory");
}
__device__ __forceinline__ unsigned ld_acq1(const void* p) {
    unsigned v;
    asm volatile("ld.acquire.gpu.global.u32 %0, [%1];" : "=r"(v) : "l"(p) : "memory");
    return v;
}
__device__ __forceinline__ void st_rlx4(void* p, uint4 v) {
    asm volatile("st.relaxed.gpu.global.v4.u32 [%0], {%1,%2,%3,%4};" ::"l"(p), "r"(v.x), "r"(v.y), "r"(v.z), "r"(v.w) : "memory");
}
__device__ __forceinline__ void st_rlx2(void* p, uint32_t a, uint32_t b) {
    asm volatile("st.relaxed.gpu.global.v2.u32 [%0], {%1,%2};" ::"l"(p), "r"(a), "r"(b) : "memory");
}
__device__ __forceinline__ void st_rlx_unit(void* p, uint32_t a, uint32_t b) {
    unsigned long long v = (unsigned long long)a | ((unsigned long long)b << 32);
    asm volatile("st.relaxed.gpu.global.u64 [%0], %1;" ::"l"(p), "l"(v) : "memory");
}
__device__ __forceinline__ uint2 ld_rlx_unit(const void* p) {
    unsigned long long a;
    asm volatile("ld.relaxed.gpu.global.u64 %0, [%1];" : "=l"(a) : "l"(p) : "memory");
    return make_uint2((uint32_t)a, (uint32_t)(a >> 32));
}
__device__ __forceinline__ uint4 ld_rlx_units2(const void* p) {
    unsigned long long a, b;
    asm volatile("ld.relaxed.gpu.global.v2.u64 {%0,%1}, [%2];" : "=l"(a), "=l"(b) : "l"(p) : "memory");
    return make_uint4((uint32_t)a, (uint32_t)(a >> 32), (uint32_t)b, (uint32_t)(b >> 32));
}
__device__ __forceinline__ void st_rlx1_p(void* p, uint32_t a, bool pred) {
    asm volatile("{\n.reg .pred q;\nsetp.ne.u32 q, %2, 0;\n@q st.relaxed.gpu.global.u32 [%0], %1;\n}" ::"l"(p), "r"(a), "r"((uint32_t)pred) : "memory");
}
__device__ __forceinline__ uint32_t umax4(uint4 v) { return max(max(v.x, v.y), max(v.z, v.w)); }
__device__ __forceinline__ uint32_t canon(float f) {
    uint32_t u = __float_as_uint(f);
    return u == EMPTY ? 0x7FFFFFFFu : u;
}
__device__ __forceinline__ uint32_t pack_bf(float lo, float hi) {
    uint32_t u;
    asm("cvt.rn.bf16x2.f32 %0, %1, %2;" : "=r"(u) : "f"(hi), "f"(lo));
    return u;
}
__device__ __forceinline__ float bfr(float x) { return __uint_as_float(pack_bf(0.0f, x)); }
__device__ __forceinline__ float bf_lo(uint32_t u) { return __uint_as_float(u << 16); }
__device__ __forceinline__ float bf_hi(uint32_t u) { return __uint_as_float(u & 0xFFFF0000u); }
__device__ __forceinline__ uint32_t badd2(uint32_t a, uint32_t b) { uint32_t d; asm("add.rn.bf16x2 %0, %1, %2;" : "=r"(d) : "r"(a), "r"(b)); return d; }
__device__ __forceinline__ uint32_t bsub2(uint32_t a, uint32_t b) { uint32_t d; asm("sub.rn.bf16x2 %0, %1, %2;" : "=r"(d) : "r"(a), "r"(b)); return d; }
__device__ __forceinline__ uint32_t bmul2(uint32_t a, uint32_t b) { uint32_t d; asm("mul.rn.bf16x2 %0, %1, %2;" : "=r"(d) : "r"(a), "r"(b)); return d; }
__device__ __forceinline__ float ex2(float x) {
    float y;
    asm("ex2.approx.ftz.f32 %0, %1;" : "=f"(y) : "f"(x));
    return y;
}
__device__ __forceinline__ float fdiv(float a, float b) {
    float y;
    asm("div.full.f32 %0, %1, %2;" : "=f"(y) : "f"(a), "f"(b));
    return y;
}
__device__ __forceinline__ float fsqrt(float a) {
    float y;
    asm("sqrt.approx.f32 %0, %1;" : "=f"(y) : "f"(a));
    return y;
}
__device__ __forceinline__ float frcp(float a) {
    float y;
    asm("rcp.approx.ftz.f32 %0, %1;" : "=f"(y) : "f"(a));
    return y;
}
__device__ __forceinline__ uint32_t pin(uint32_t v) {
    uint32_t r;
    asm volatile("mov.u32 %0, %1;" : "=r"(r) : "r"(v));
    return r;
}
template <class T>
__device__ __forceinline__ T* pinp(T* p) {
    unsigned long long r;
    asm volatile("mov.u64 %0, %1;" : "=l"(r) : "l"(p));
    return reinterpret_cast<T*>(r);
}
__device__ __forceinline__ float lds1(uint32_t a) { float v; asm volatile("ld.shared.f32 %0, [%1];" : "=f"(v) : "r"(a) : "memory"); return v; }
__device__ __forceinline__ uint2 lds2(uint32_t a) { uint2 v; asm volatile("ld.shared.v2.u32 {%0,%1}, [%2];" : "=r"(v.x), "=r"(v.y) : "r"(a) : "memory"); return v; }
__device__ __forceinline__ float silu_f(float x) { return fdiv(x, 1.0f + ex2(-x * kLog2e)); }

__device__ __forceinline__ void ldsm4(uint32_t a, uint32_t& r0, uint32_t& r1, uint32_t& r2, uint32_t& r3) {
    asm volatile("ldmatrix.sync.aligned.m8n8.x4.shared.b16 {%0,%1,%2,%3}, [%4];" : "=r"(r0), "=r"(r1), "=r"(r2), "=r"(r3) : "r"(a) : "memory");
}
__device__ __forceinline__ void ldsm4t(uint32_t a, uint32_t* r) {
    asm volatile("ldmatrix.sync.aligned.m8n8.x4.trans.shared.b16 {%0,%1,%2,%3}, [%4];" : "=r"(r[0]), "=r"(r[1]), "=r"(r[2]), "=r"(r[3]) : "r"(a) : "memory");
}
__device__ __forceinline__ void mma16816(float* c, uint32_t a0, uint32_t a1, uint32_t a2, uint32_t a3, uint32_t b0, uint32_t b1) {
    asm("mma.sync.aligned.m16n8k16.row.col.f32.bf16.bf16.f32 {%0,%1,%2,%3}, {%4,%5,%6,%7}, {%8,%9}, {%0,%1,%2,%3};"
                 : "+f"(c[0]), "+f"(c[1]), "+f"(c[2]), "+f"(c[3])
                 : "r"(a0), "r"(a1), "r"(a2), "r"(a3), "r"(b0), "r"(b1));
}

__device__ __forceinline__ void ln_stats(const uint2 (&v)[9], float& mean, float& rs) {
    float s = 0.f;
#pragma unroll
    for (int i = 0; i < 9; i++) s += (bf_lo(v[i].x) + bf_hi(v[i].x)) + (bf_lo(v[i].y) + bf_hi(v[i].y));
    s += __shfl_xor_sync(FULLM, s, 1);
    s += __shfl_xor_sync(FULLM, s, 2);
    s += __shfl_xor_sync(FULLM, s, 8);
    s += __shfl_xor_sync(FULLM, s, 16);
    mean = s * (1.0f / kD);
    float q = 0.f;
#pragma unroll
    for (int i = 0; i < 9; i++) {
        const float a = bf_lo(v[i].x) - mean, b = bf_hi(v[i].x) - mean, c = bf_lo(v[i].y) - mean, d = bf_hi(v[i].y) - mean;
        q += (a * a + b * b) + (c * c + d * d);
    }
    q += __shfl_xor_sync(FULLM, q, 1);
    q += __shfl_xor_sync(FULLM, q, 2);
    q += __shfl_xor_sync(FULLM, q, 8);
    q += __shfl_xor_sync(FULLM, q, 16);
    rs = fdiv(1.0f, bfr(fsqrt(bfr(bfr(q * (1.0f / kD)) + 1e-5f))));
}

__device__ __forceinline__ void poll_mod(const uint2* p, unsigned tag, uint32_t (&sh)[18], uint32_t (&c1)[18]) {
    int spin = 0;
    while (true) {
        uint32_t bad = 0;
#pragma unroll
        for (int i = 0; i < 18; i++) {
            const uint2 a = ld_rlx_unit(p + 4 * i), b = ld_rlx_unit(p + kD / 2 + 4 * i);
            bad |= (a.y ^ tag) | (b.y ^ tag);
            sh[i] = a.x; c1[i] = b.x;
        }
        if (__all_sync(FULLM, bad == 0)) break;
        if (++spin > SPIN_LIMIT) __trap();
    }
#pragma unroll
    for (int i = 0; i < 18; i++) c1[i] = badd2(c1[i], 0x3F803F80u);
}

__device__ __forceinline__ float owner_sum(const float* src, int lane) {
    uint4 v0 = make_uint4(EMPTY, EMPTY, EMPTY, EMPTY), v1 = v0;
    int spin = 0;
    while (true) {
        repoll4(v0, src);
        repoll4(v1, src + 128);
        if (__all_sync(FULLM, max(umax4(v0), umax4(v1)) != EMPTY)) break;
        if (++spin > SPIN_LIMIT) __trap();
    }
    const float s0 = __uint_as_float(v0.x) + __uint_as_float(v1.x), s1 = __uint_as_float(v0.y) + __uint_as_float(v1.y);
    const float s2 = __uint_as_float(v0.z) + __uint_as_float(v1.z), s3 = __uint_as_float(v0.w) + __uint_as_float(v1.w);
    const bool b1 = lane & 2, b2 = lane & 4;
    const float k0 = (b1 ? s2 : s0) + __shfl_xor_sync(FULLM, b1 ? s0 : s2, 2);
    const float k1 = (b1 ? s3 : s1) + __shfl_xor_sync(FULLM, b1 ? s1 : s3, 2);
    float s = (b2 ? k1 : k0) + __shfl_xor_sync(FULLM, b2 ? k0 : k1, 4);
    s += __shfl_xor_sync(FULLM, s, 8);
    s += __shfl_xor_sync(FULLM, s, 16);
    return s;
}
__device__ __forceinline__ float pick(const float* c, int t) { return (t & 2) ? ((t & 1) ? c[3] : c[2]) : ((t & 1) ? c[1] : c[0]); }

__global__ void __launch_bounds__(NTHR, 1)
fused_kernel(const __grid_constant__ CUtensorMap tm_w1, const __grid_constant__ CUtensorMap tm_w3,
             const __grid_constant__ CUtensorMap tm_wo, const __grid_constant__ CUtensorMap tm_w2,
             const __grid_constant__ CUtensorMap tm_wq, const __grid_constant__ CUtensorMap tm_wm,
             const bf16* __restrict__ x, const bf16* __restrict__ kc, const bf16* __restrict__ vc,
             const bf16* __restrict__ cvec, const bf16* __restrict__ wmod, bf16* __restrict__ out) {
    extern __shared__ __align__(1024) unsigned char smem[];
    const uint32_t sbase = (uint32_t)__cvta_generic_to_shared(smem);
    const uint32_t bar_full = sbase + BAR_FULL, bar_empty = sbase + BAR_EMPTY;
    const int tid = pin(threadIdx.x), lane = tid & 31, warp = tid >> 5;
    const int j = pin(blockIdx.x);
    volatile int* s_avg = reinterpret_cast<volatile int*>(smem + SM_AVG);

    if (warp >= 8) {
        asm volatile("setmaxnreg.dec.sync.aligned.u32 40;");
        if (warp > 8) {
            constexpr int MONW = 9 + (NITEM - NPINIT) % 3;
            if (lane == 0) {
                if (warp == MONW) { s_avg[0] = -(1 << 20); s_avg[1] = 0; }
#pragma unroll 1
                for (int i = NPINIT + warp - 9; i < NBAR; i += 3) mbar_init(bar_full + i * 8, 1);
                asm volatile("fence.mbarrier_init.release.cluster;" ::: "memory");
                asm volatile("fence.proxy.async.shared::cta;" ::: "memory");
            }
            __syncwarp();
            asm volatile("bar.arrive 2, 128;" ::: "memory");
            asm volatile("bar.arrive 4, 352;" ::: "memory");
            if (warp == MONW && lane == 0) {
                mbar_wait1(bar_empty);
                unsigned pr = ld_rlx1(&g_prog);
                const unsigned pbase = pr & ~(unsigned)(128 * NCTA - 1);
                int spin = 0;
                while (!s_avg[1]) {
                    s_avg[0] = (int)((pr - pbase) >> 7) + LAG;
                    __nanosleep(MONNS);
                    pr = ld_rlx1(&g_prog);
                    if (++spin > SPIN_LIMIT) __trap();
                }
            }
            return;
        }
        const int grp = j >> 3, bb = (j >> 2) & 1, sp = j & 3;
        const size_t kvoff = ((size_t)(bb * 16 + grp) * kSK + (size_t)sp * 2048) * 128;
        const unsigned char* kp = reinterpret_cast<const unsigned char*>(kc + kvoff);
        const unsigned char* vp = reinterpret_cast<const unsigned char*>(vc + kvoff);
        uint64_t pol;
        asm volatile("createpolicy.fractional.L2::evict_first.b64 %0, 1.0;" : "=l"(pol));
        if (lane == 0) {
            mbar_init(bar_full, 1);
            asm volatile("fence.proxy.async.shared::cta;" ::: "memory");
            mbar_expect_tx(bar_full, SLOT);
            bulk_load(sbase + item_off(0), kp, SLOT, bar_full, pol);
            asm volatile("prefetch.tensormap [%0];" ::"l"(&tm_wq) : "memory");
            mbar_init(sbase + BAR_WQ, 1);
            mbar_init(sbase + BAR_WQ + 8, 1);
            asm volatile("fence.proxy.async.shared::cta;" ::: "memory");
            mbar_expect_tx(sbase + BAR_WQ, 2 * BOXB);
            mbar_expect_tx(sbase + BAR_WQ + 8, 2 * BOXB);
#pragma unroll
            for (int i = 0; i < 4; i++) tma2d(sbase + OFF_WQ + i * BOXB, &tm_wq, grp * 256 + i * 64, (j & 7) * 72, sbase + BAR_WQ + (i >> 1) * 8);
#pragma unroll
            for (int i = 1; i < NPINIT; i++) mbar_init(bar_full + i * 8, 1);
            mbar_init(sbase + BAR_CRIT, 1);
            asm volatile("fence.mbarrier_init.release.cluster;" ::: "memory");
            asm volatile("fence.proxy.async.shared::cta;" ::: "memory");
            asm volatile("red.relaxed.gpu.global.add.u32 [%0], 1;" ::"l"(&g_prog) : "memory");
        }
        __syncwarp();
        asm volatile("bar.arrive 3, 288;" ::: "memory");
        TS(13);
        if (lane == 0) {
#pragma unroll 1
            for (int i = 1; i < NPINIT; i++) {
                if (i - DHEAD >= -2) mbar_wait1(bar_full + (i - DHEAD) * 8);
                mbar_expect_tx(bar_full + i * 8, SLOT);
                bulk_load(sbase + item_off(i), ((i & 1) ? vp : kp) + (size_t)(i >> 1) * SLOT, SLOT, bar_full + i * 8, pol);
                asm volatile("red.relaxed.gpu.global.add.u32 [%0], 1;" ::"l"(&g_prog) : "memory");
            }
        }
        __syncwarp();
        asm volatile("bar.sync 2, 128;" ::: "memory");
        if (lane == 0) {
            int pf = -2;
#pragma unroll 1
            for (int i = NPINIT; i < NKV; i++) {
                if (i >= NS + 2 && !mbar_test(bar_empty + prev_user(i) * 8)) {
                    int spin = 0;
                    long long tl = clock64();
                    pf = max(pf, i);
                    while (!mbar_test(bar_empty + prev_user(i) * 8)) {
                        const long long now = clock64();
                        const bool go = (pf - DHEAD < i) ? (mbar_test(bar_full + (pf - DHEAD) * 8) != 0) : (now - tl >= PFCLK);
                        if (go && pf < i + 12 && pf < NKV) {
                            asm volatile("cp.async.bulk.prefetch.L2.global [%0], %1;" ::"l"(((pf & 1) ? vp : kp) + (size_t)(pf >> 1) * SLOT), "r"(SLOT) : "memory");
                            pf++;
                            tl = now;
                        }
                        if (++spin > (SPIN_LIMIT << 4)) __trap();
                    }
                }
                if (i == NS - 1) mbar_wait1(sbase + BAR_CRIT);
                const int avg = *s_avg;
                int d = DHEAD;
                if (avg >= 0) d = min(max(DEPTH + avg - i, DMIN), DMAX);
                if (i - d >= pf) mbar_wait1(bar_full + (i - d) * 8);
                mbar_expect_tx(bar_full + i * 8, SLOT);
                bulk_load(sbase + item_off(i), ((i & 1) ? vp : kp) + (size_t)(i >> 1) * SLOT, SLOT, bar_full + i * 8, pol);
                asm volatile("red.relaxed.gpu.global.add.u32 [%0], 1;" ::"l"(&g_prog) : "memory");
                if (i >= 20 && i < 24) {
                    if (i == 20) { mbar_wait1(bar_empty + NS * 8); mbar_wait1(bar_empty + (NS + 1) * 8); }
                    if (j >= 56) {
                        if (i == 20) mbar_expect_tx(sbase + BAR_WM, 576 * 64);
                        tma2d(sbase + OFF_WM + (i - 20) * 144 * 64, &tm_wm, 2 * kD + 32 * (j - 56), (i - 20) * 144, sbase + BAR_WM);
                    }
                } else if (i == 8) {
                    asm volatile("prefetch.tensormap [%0];" ::"l"(&tm_wm) : "memory");
                } else if (i == 30) {
                    asm volatile("prefetch.tensormap [%0];" ::"l"(&tm_wo) : "memory");
                } else if (i == 34) {
                    asm volatile("prefetch.tensormap [%0];" ::"l"(&tm_w3) : "memory");
                    asm volatile("prefetch.tensormap [%0];" ::"l"(&tm_w1) : "memory");
                    asm volatile("prefetch.tensormap [%0];" ::"l"(&tm_w2) : "memory");
                }
            }
            int freed = 0;
            if (j >= 56) mbar_wait1(sbase + BAR_WMDONE);
#pragma unroll 1
            for (int wi = 0; wi < NW; wi++) {
                const int item = NKV + wi;
                const int dst = wi < 2 ? OFF_WO + wi * 64 * 288 : (wi - 2) * QB;
                const int bytes = wi < 2 ? 64 * 288 : QB;
                const int need = wi < 2 ? 0 : (dst + bytes - 1) / SLOT + 1;
                while (freed < need) { mbar_wait1(bar_empty + (NKV - NS + freed) * 8); freed++; }
                if (wi == 6) mbar_wait1(sbase + BAR_GATE);
                if (wi != 7) mbar_wait1(bar_full + (item - (wi < 2 ? WOD : min(max(WDEPTH + *s_avg - item, WMIN), WMAX))) * 8);
                asm volatile("red.relaxed.gpu.global.add.u32 [%0], 1;" ::"l"(&g_prog) : "memory");
                const uint32_t fb = bar_full + item * 8;
                mbar_expect_tx(fb, bytes);
                if (wi < 2) {
                    tma2d(sbase + dst, &tm_wo, (j & 3) * 144, (j >> 2) * 128 + wi * 64, fb);
                } else if (wi >= 6) {
                    tma2d(sbase + dst, &tm_w2, (j & 3) * 144, (j >> 2) * 144 + (wi - 6) * 72, fb);
                } else {
                    tma2d(sbase + dst, (wi & 4) ? &tm_w3 : &tm_w1, (j >> 2) * 144, (j & 3) * 144 + (wi & 1) * 72, fb);
                }
            }
            asm volatile("red.relaxed.gpu.global.add.u32 [%0], %1;" ::"l"(&g_prog), "n"(128 - NITEM) : "memory");
            s_avg[1] = 1;
        }
        __syncwarp();
        TS(9);
        return;
    }

    asm volatile("setmaxnreg.inc.sync.aligned.u32 232;");
    const int g = lane >> 2, t = lane & 3, r8 = lane & 7, mi = lane >> 3;
    const int lq = (g & 1) * 144 + (g >> 1) * 36 + 9 * t;

    if (warp == 0) TS(0);
    unsigned tag;
    {
        const int rk = j & 7, cgp = j >> 3;
#pragma unroll
        for (int i = 0; i < 3; i++) {
            const int u = tid + 256 * i, r = u / 9, ch = u - r * 9;
            if (u < 648) cp16(sbase + OFF_WC + r * CPITCH + ch * 16, wmod + (size_t)(rk * 72 + r) * kMOD + cgp * 72 + ch * 8);
        }
        cp_commit();
        uint32_t cb[10];
        {
            const uint32_t* cp = reinterpret_cast<const uint32_t*>(cvec) + (g & 1) * (kD / 2) + rk * 36 + t;
#pragma unroll
            for (int i = 0; i < 9; i++) cb[i] = __ldg(cp + 4 * i);
        }
        tag = ld_rlx1(&g_arrive);
        uint2 xv[9];
        if (warp < 3) {
            const uint2* xp = reinterpret_cast<const uint2*>(x) + lq;
#pragma unroll
            for (int i = 0; i < 9; i++) xv[i] = __ldg(xp + i);
        }
        const int hb = tid >= 36, hp = min(tid, 71) - hb * 36;
        const uint32_t xpair = __ldg(reinterpret_cast<const uint32_t*>(x) + hb * (kD / 2) + rk * 36 + hp);
        st_rlx4(reinterpret_cast<uint4*>(g_qp + j * 512) + tid, make_uint4(0, 0, 0, 0));
        if (tid < 72) st_rlx4(reinterpret_cast<uint4*>(g_mc + j * 144) + tid, make_uint4(0, 0, 0, 0));
        tag = (tag >> 10) + 1;
#pragma unroll
        for (int i = 0; i < 9; i++) cb[i] = pack_bf(silu_f(bf_lo(cb[i])), silu_f(bf_hi(cb[i])));
        cb[9] = 0u;
        const int krow = r8 + 8 * (mi >> 1);
        cp_wait<0>();
        asm volatile("bar.sync 3, 288;" ::: "memory");
        if (warp == 0) TS(14);
        if (warp < 5) {
            float c[4] = {0.f, 0.f, 0.f, 0.f};
            const uint32_t a = sbase + OFF_WC + (2 * warp + (mi & 1)) * 16;
            uint32_t w[5][4];
#pragma unroll
            for (int ks = 0; ks < 5; ks++) ldsm4t(a + ((ks < 4) ? ks * 16 + krow : 64 + r8) * CPITCH, w[ks]);
#pragma unroll
            for (int ks = 0; ks < 5; ks++) mma16816(c, w[ks][0], w[ks][1], w[ks][2], w[ks][3], cb[2 * ks], cb[2 * ks + 1]);
            const float v = (t & 2) ? ((t & 1) ? c[3] : c[2]) : ((t & 1) ? c[1] : c[0]);
            if (warp < 4 || t < 2) st_rlx_unit(g_mc + (j * 2 + (t & 1)) * 72 + 16 * warp + 8 * (t >> 1) + g, __float_as_uint(v), tag);
        }
        if (warp == 0) TS(1);
        asm volatile("fence.proxy.async.shared::cta;" ::: "memory");
        uint32_t ln = 0u;
        if (warp < 3) {
            float mean, rs;
            ln_stats(xv, mean, rs);
            const float m_b = __shfl_sync(FULLM, mean, hb * 4), r_b = __shfl_sync(FULLM, rs, hb * 4);
            const uint32_t d = bsub2(xpair, pack_bf(m_b, m_b));
            ln = pack_bf(bf_lo(d) * r_b, bf_hi(d) * r_b);
        }
        uint32_t w[5][2][4];
        mbar_wait(sbase + BAR_WQ + (warp >> 2) * 8);
        if (warp == 0) TS(17);
        {
            const uint32_t a = sbase + OFF_WQ + (warp >> 1) * BOXB + ((((warp & 1) * 4 + (mi & 1)) ^ r8) << 4);
#pragma unroll
            for (int ks = 0; ks < 5; ks++) {
                const uint32_t r = a + ((ks < 4) ? ks * 16 + krow : 64 + r8) * 128;
                ldsm4t(r, w[ks][0]);
                ldsm4t(r ^ 32, w[ks][1]);
            }
        }
        if (warp < 3) {
            const uint2* p = g_mc + (rk * 16 + hb) * 72 + 2 * hp;
            float s0, s1, c0, c1;
            int spin = 0;
            while (true) {
                uint32_t bad = 0;
                s0 = s1 = c0 = c1 = 0.f;
#pragma unroll
                for (int k = 0; k < 8; k++) {
                    const uint4 a = ld_rlx_units2(p + k * 144), b = ld_rlx_units2(p + 64 * 144 + k * 144);
                    bad |= (a.y ^ tag) | (a.w ^ tag) | (b.y ^ tag) | (b.w ^ tag);
                    s0 += __uint_as_float(a.x); s1 += __uint_as_float(a.z);
                    c0 += __uint_as_float(b.x); c1 += __uint_as_float(b.z);
                }
                if (__all_sync(FULLM, bad == 0)) break;
                if (++spin > SPIN_LIMIT) __trap();
            }
            const uint32_t h = badd2(bmul2(ln, badd2(pack_bf(c0, c1), 0x3F803F80u)), pack_bf(s0, s1));
            if (tid < 72) reinterpret_cast<uint32_t*>(smem + SM_X1)[hb * 36 + hp] = h;
        }
        cons_bar();
        if (tid == 224) mbar_arrive(sbase + BAR_CRIT);
        if (warp == 0) TS(2);
        {
            const uint32_t* p = reinterpret_cast<const uint32_t*>(smem + SM_X1) + (g & 1) * 36 + t;
            float c[2][4] = {{0.f, 0.f, 0.f, 0.f}, {0.f, 0.f, 0.f, 0.f}};
#pragma unroll
            for (int ks = 0; ks < 5; ks++) {
                const uint32_t b0 = p[8 * ks], b1 = ks < 4 ? p[8 * ks + 4] : 0u;
                mma16816(c[0], w[ks][0][0], w[ks][0][1], w[ks][0][2], w[ks][0][3], b0, b1);
                mma16816(c[1], w[ks][1][0], w[ks][1][1], w[ks][1][2], w[ks][1][3], b0, b1);
            }
            uint2* d = g_qp + (j * 2 + (t & 1)) * 256 + 32 * warp + 8 * (t >> 1) + g;
#pragma unroll
            for (int m = 0; m < 2; m++) {
                const float v = (t & 2) ? ((t & 1) ? c[m][3] : c[m][2]) : ((t & 1) ? c[m][1] : c[m][0]);
                st_rlx_unit(d + 16 * m, __float_as_uint(v), tag);
            }
        }
        if (warp == 0) TS(15);
        if (warp >= 4) {
            const int k = tid - 128;
            const uint2* p = g_qp + ((j >> 3) * 16 + ((j >> 2) & 1)) * 256 + 2 * k;
            float q0, q1;
            int spin = 0;
            while (true) {
                uint32_t bad = 0;
                q0 = q1 = 0.f;
#pragma unroll
                for (int kb = 0; kb < 8; kb++) {
                    const uint4 a = ld_rlx_units2(p + kb * 512);
                    bad |= (a.y ^ tag) | (a.w ^ tag);
                    q0 += __uint_as_float(a.x); q1 += __uint_as_float(a.z);
                }
                if (__all_sync(FULLM, bad == 0)) break;
                if (++spin > SPIN_LIMIT) __trap();
            }
            reinterpret_cast<uint32_t*>(smem + SM_QS)[k] = pack_bf(q0, q1);
        }
        asm volatile("bar.sync 4, 352;" ::: "memory");
    }
    if (warp == 0) TS(3);

    const bool owner = j < NOWN && (warp & 3) == 0;
    const int ocol = 16 * j + 8 * (warp >> 2) + (lane & 1) * 4 + (lane & 2) + ((lane >> 2) & 1);
    uint32_t sh2[18], c12[18];
    float o_x = 0.f, o_ga = 0.f, o_gb = 0.f;
    {
        const int np = g >> 1;
        uint32_t qf[16];
#pragma unroll
        for (int c = 0; c < 16; c++) qf[c] = reinterpret_cast<const uint32_t*>(smem + SM_QS)[(g & 1) * 64 + 4 * (c ^ np) + t];
        const bool is_lo = (t == (g >> 2)), is_hi = (t == 2 + (g >> 2));
        const int e = np & 1;
        const uint32_t em = e ? 0xFFFF0000u : 0x0000FFFFu;
        const uint32_t mlo = is_lo ? em : 0u, mhi = is_hi ? em : 0u;
        const uint32_t koff0 = r8 * 256 + ((mi ^ r8) << 4), koff1 = r8 * 256 + (((mi | 4) ^ r8) << 4);
        uint32_t voff[4];
#pragma unroll
        for (int c = 0; c < 4; c++) voff[c] = ((mi & 1) * 8 + r8) * 256 + (((2 * c + (mi >> 1)) ^ r8) << 4);

        float O[16][4];
#pragma unroll
        for (int c = 0; c < 16; c++) { O[c][0] = O[c][1] = O[c][2] = O[c][3] = 0.f; }
        float m_run = -INFINITY, l_run = 0.f;
        const bool valid = is_lo || is_hi;

#pragma unroll 1
        for (int it = 0; it < 4; it++) {
            const int iK = 2 * (warp + 8 * it), iV = iK + 1;
            const uint32_t kb = sbase + item_off(iK), vb = sbase + item_off(iV);
            float S[8][4];
#pragma unroll
            for (int n = 0; n < 8; n++) { S[n][0] = S[n][1] = S[n][2] = S[n][3] = 0.f; }
            mbar_wait(bar_full + iK * 8);
#pragma unroll
            for (int s2 = 0; s2 < 4; s2++) {
                const uint32_t a = kb + ((s2 & 1) ? koff1 : koff0) + (s2 >> 1) * 128;
#pragma unroll
                for (int n = 0; n < 8; n++) {
                    uint32_t b0, b1, b2, b3;
                    ldsm4(a + n * 2048, b0, b1, b2, b3);
                    mma16816(S[n], qf[4 * s2], qf[(4 * s2) ^ 4], qf[4 * s2 + 1], qf[(4 * s2 + 1) ^ 4], b0, b1);
                    mma16816(S[n], qf[4 * s2 + 2], qf[(4 * s2 + 2) ^ 4], qf[4 * s2 + 3], qf[(4 * s2 + 3) ^ 4], b2, b3);
                }
            }
            __syncwarp();
            if (lane == 0) mbar_arrive(bar_empty + iK * 8);
            float sc[8];
            float mx = -INFINITY;
#pragma unroll
            for (int n = 0; n < 8; n++) {
                const float a = e ? S[n][1] : S[n][0], b = e ? S[n][3] : S[n][2];
                sc[n] = bfr(bfr(is_lo ? a : b) * kScale);
                mx = fmaxf(mx, sc[n]);
            }
            mx = valid ? fmaxf(mx, m_run) : m_run;
            float4 pv0 = make_float4(0.f, 0.f, 0.f, 0.f), pv1 = pv0;
            float2 pml = make_float2(-INFINITY, 0.f);
            if (it == 3 && warp > 0) {
                mbar_wait(sbase + BAR_CHAIN + (warp - 1) * 8);
                pv0 = *reinterpret_cast<const float4*>(smem + SM_MRG + lane * 32);
                pv1 = *reinterpret_cast<const float4*>(smem + SM_MRG + lane * 32 + 16);
                pml = *reinterpret_cast<const float2*>(smem + SM_MRG + 1024 + lane * 8);
                mx = fmaxf(mx, pml.x);
            }
            mx = fmaxf(mx, __shfl_xor_sync(FULLM, mx, 1));
            mx = fmaxf(mx, __shfl_xor_sync(FULLM, mx, 2));
            mx = fmaxf(mx, __shfl_xor_sync(FULLM, mx, 8));
            mx = fmaxf(mx, __shfl_xor_sync(FULLM, mx, 16));
            const float corr = ex2((m_run - mx) * kLog2e);
            m_run = mx;
            uint32_t pk[8];
            float ps = 0.f;
#pragma unroll
            for (int n = 0; n < 8; n++) {
                const float p = ex2((sc[n] - mx) * kLog2e);
                ps += p;
                pk[n] = pack_bf(p, p);
            }
            l_run = l_run * corr + (valid ? ps : 0.f);
            if (__any_sync(FULLM, corr != 1.0f)) {
#pragma unroll
                for (int c = 0; c < 16; c++) { O[c][0] *= corr; O[c][1] *= corr; O[c][2] *= corr; O[c][3] *= corr; }
            }
            if (it == 3) {
                const float f_p = ex2((pml.x - mx) * kLog2e);
                O[0][0] = fmaf(pv0.x, f_p, O[0][0]);   O[0][1] = fmaf(pv0.y, f_p, O[0][1]);
                O[4][0] = fmaf(pv0.z, f_p, O[4][0]);   O[4][1] = fmaf(pv0.w, f_p, O[4][1]);
                O[8][0] = fmaf(pv1.x, f_p, O[8][0]);   O[8][1] = fmaf(pv1.y, f_p, O[8][1]);
                O[12][0] = fmaf(pv1.z, f_p, O[12][0]); O[12][1] = fmaf(pv1.w, f_p, O[12][1]);
                l_run += __shfl_xor_sync(FULLM, l_run, 1);
                l_run += __shfl_xor_sync(FULLM, l_run, 2);
                l_run += __shfl_xor_sync(FULLM, l_run, 8);
                l_run += __shfl_xor_sync(FULLM, l_run, 16);
                l_run = fmaf(pml.y, f_p, l_run);
            }
            mbar_wait(bar_full + iV * 8);
#pragma unroll
            for (int u = 0; u < 4; u++) {
                const uint32_t a0 = pk[2 * u] & mlo, a1 = pk[2 * u] & mhi, a2 = pk[2 * u + 1] & mlo, a3 = pk[2 * u + 1] & mhi;
#pragma unroll
                for (int cp = 0; cp < 8; cp++) {
                    uint32_t b[4];
                    ldsm4t(vb + voff[cp & 3] + u * 4096 + (cp >> 2) * 128, b);
                    mma16816(O[2 * cp], a0, a1, a2, a3, b[0], b[1]);
                    mma16816(O[2 * cp + 1], a0, a1, a2, a3, b[2], b[3]);
                }
            }
            __syncwarp();
            if (lane == 0) mbar_arrive(bar_empty + iV * 8);

            if (it == 1 && warp == 6 && j >= 56) {
                uint32_t sc[18];
                const uint2* cp = reinterpret_cast<const uint2*>(cvec) + lq;
#pragma unroll
                for (int i = 0; i < 9; i++) {
                    const uint2 v = __ldg(cp + i);
                    sc[2 * i] = pack_bf(silu_f(bf_lo(v.x)), silu_f(bf_hi(v.x)));
                    sc[2 * i + 1] = pack_bf(silu_f(bf_lo(v.y)), silu_f(bf_hi(v.y)));
                }
                mbar_wait(sbase + BAR_WM);
                const int r0 = (r8 >> 1) * 36 + (r8 & 1) + 2 * (mi >> 1);
                uint32_t a = sbase + OFF_WM + r0 * 64 + (((mi & 1) ^ ((r0 >> 1) & 3)) << 4);
                float acc[8] = {0.f, 0.f, 0.f, 0.f, 0.f, 0.f, 0.f, 0.f};
#pragma unroll 1
                for (int q = 0; q < 4; q++) {
                    float c[2][4] = {{0.f, 0.f, 0.f, 0.f}, {0.f, 0.f, 0.f, 0.f}};
#pragma unroll
                    for (int i = 0; i < 9; i++) {
                        uint32_t w0[4], w1[4];
                        ldsm4t((a + i * 256) ^ ((i & 1) * 32), w0);
                        ldsm4t((a + i * 256) ^ ((i & 1) * 32) ^ 32, w1);
                        mma16816(c[0], w0[0], w0[1], w0[2], w0[3], sc[2 * i], sc[2 * i + 1]);
                        mma16816(c[1], w1[0], w1[1], w1[2], w1[3], sc[2 * i], sc[2 * i + 1]);
                    }
                    if (t == q) {
#pragma unroll
                        for (int k = 0; k < 8; k++) acc[k] = c[k >> 2][k & 3];
                    }
                    a += 144 * 64;
                }
                __syncwarp();
                if (lane == 0) mbar_arrive(sbase + BAR_WMDONE);
#pragma unroll
                for (int k = 0; k < 8; k++) {
                    acc[k] += __shfl_xor_sync(FULLM, acc[k], 1);
                    acc[k] += __shfl_xor_sync(FULLM, acc[k], 2);
                }
                const float v0 = (t & 2) ? ((t & 1) ? acc[6] : acc[4]) : ((t & 1) ? acc[2] : acc[0]);
                const float v1 = (t & 2) ? ((t & 1) ? acc[7] : acc[5]) : ((t & 1) ? acc[3] : acc[1]);
                const float n0 = __shfl_xor_sync(FULLM, v0, 4), n1 = __shfl_xor_sync(FULLM, v1, 4);
                const uint32_t u = (g & 1) ? pack_bf(n1, v1) : pack_bf(v0, n0);
                st_rlx_unit(g_mod + (g & 1) * (kMOD / 2) + kD + 16 * (j - 56) + 4 * t + (g >> 1), u, tag);
            }
            if (it == 2) {
                poll_mod(g_mod + (g & 1) * (kMOD / 2) + 3 * (kD / 2) + (j & 3) * 72 + t, tag, sh2, c12);
                if (owner) {
                    const int b = ocol >= kD, n = ocol - b * kD;
                    const uint2* p = g_mod + b * (kMOD / 2) + (2 * kD + n) / 2;
                    uint2 ua, ub2;
                    int spin = 0;
                    while (true) {
                        ua = ld_rlx_unit(p);
                        ub2 = ld_rlx_unit(p + 3 * (kD / 2));
                        if (__all_sync(FULLM, ua.y == tag && ub2.y == tag)) break;
                        if (++spin > SPIN_LIMIT) __trap();
                    }
                    o_ga = (n & 1) ? bf_hi(ua.x) : bf_lo(ua.x);
                    o_gb = (n & 1) ? bf_hi(ub2.x) : bf_lo(ub2.x);
                    o_x = __bfloat162float(x[ocol]);
                }
            }
            if (it == 1) {
                const uint4 ev = make_uint4(EMPTY, EMPTY, EMPTY, EMPTY);
                if (tid < 66) st_rlx4(g_x3 + j * 264 + tid * 4, ev);
                if (lane < 18) st_rlx4(g_x7 + j * 576 + warp * 72 + lane * 4, ev);
                if (j < NOWN) {
                    st_rlx4(&g_xr[lane >> 4][j * 512 + warp * 64 + (lane & 15) * 4], ev);
                    if (lane < 2) st_rlx4(g_x5 + warp * kD + j * 8 + lane * 4, ev);
                }
                __syncwarp();
                if (lane == 0) {
                    __threadfence();
                    asm volatile("red.release.gpu.global.add.u32 [%0], 1;" ::"l"(&g_arrive) : "memory");
                }
                __syncwarp();
            }
        }
        if (warp == 7) TS(4);
        float Om[16][2];
#pragma unroll
        for (int c = 0; c < 16; c++) {
            Om[c][0] = O[c][0] + O[c ^ 4][2];
            Om[c][1] = O[c][1] + O[c ^ 4][3];
        }
#pragma unroll
        for (int c = 0; c < 16; c += 2) {
            Om[c][0] += __shfl_xor_sync(FULLM, Om[c ^ 1][0], 8);
            Om[c][1] += __shfl_xor_sync(FULLM, Om[c ^ 1][1], 8);
        }
#pragma unroll
        for (int c = 0; c < 16; c += 4) {
            Om[c][0] += __shfl_xor_sync(FULLM, Om[c ^ 2][0], 16);
            Om[c][1] += __shfl_xor_sync(FULLM, Om[c ^ 2][1], 16);
        }
        const float4 pv0 = make_float4(Om[0][0], Om[0][1], Om[4][0], Om[4][1]), pv1 = make_float4(Om[8][0], Om[8][1], Om[12][0], Om[12][1]);
        const float M = m_run, L = l_run;
        if (warp < 7) {
            *reinterpret_cast<float4*>(smem + SM_MRG + lane * 32) = pv0;
            *reinterpret_cast<float4*>(smem + SM_MRG + lane * 32 + 16) = pv1;
            *reinterpret_cast<float2*>(smem + SM_MRG + 1024 + lane * 8) = make_float2(M, L);
            if (warp == 0) {
                int spin = 0;
                while (!__all_sync(FULLM, (int)(ld_acq1(&g_arrive) - (tag << 10)) >= 0)) { if (++spin > SPIN_LIMIT) __trap(); }
            }
            __syncwarp();
            if (lane == 0) mbar_arrive(sbase + BAR_CHAIN + warp * 8);
        } else {
            float* dst = g_x3 + (j * 2 + (g & 1)) * 132;
            float* d = dst + 8 * np + 2 * t;
            st_rlx2(d, canon(pv0.x), canon(pv0.y));
            st_rlx2(d + 32, canon(pv0.z), canon(pv0.w));
            st_rlx2(d + 64, canon(pv1.x), canon(pv1.y));
            st_rlx2(d + 96, canon(pv1.z), canon(pv1.w));
            if (g < 2 && t == 0) st_rlx2(dst + 128, canon(M), canon(L));
            __syncwarp();
            if (lane == 0) mbar_arrive(sbase + BAR_CHAIN + 7 * 8);
            TS(20);
        }
    }

    float* xdst = pinp(&g_xr[0][(((t & 1) * 72 + (j & 3) * 18 + 2 * warp + (t >> 1)) * 32 + (j >> 2)) * 8 + g]);
    const float* osrc = pinp(&g_xr[0][(2 * j + (warp >> 2)) * 256 + lane * 4]);
    const uint32_t osa = pin(sbase + SM_QS + ((g & 1) * 64 + t) * 4);
    const uint32_t tla = pin(sbase + (r8 + 8 * (mi >> 1)) * 288 + (2 * warp + (mi & 1)) * 16);
    unsigned* x5dst = pinp(g_x5 + (lane >> 2) * kD + (ocol >> 1));
    const unsigned* x5src = pinp(g_x5 + (j & 7) * kD + min(max(tid - 64, 0), 143) * 4);
    const uint32_t x5sts = pin(sbase + SM_X1 + min(max(tid - 64, 0), 143) * 16);
    float* x7dst = pinp(g_x7 + j * 576 + (t & 1) * 144 + 16 * warp + 8 * (t >> 1) + g);
    bf16* outp = pinp(out + ocol);
    const float* x3src = pinp(g_x3 + (((j & ~7) + (warp & 1) * 4) * 2 + ((j >> 2) & 1)) * 132);
    const uint32_t xa0 = pin(sbase + SM_X1 + lq * 8), xb0 = pin(sbase + SM_X1 + ((g & 1) * 288 + (j & 3) * 72 + t) * 4);
    const int ht = min(tid, 143);
    const float* hsrc = pinp(g_x7 + (j & ~3) * 576 + ht * 2);
    const uint32_t hha = pin(sbase + SM_HH + ((g & 1) * 72 + t) * 4);
    {
        uint32_t w[8][4], w9[8][4];
        if (warp == 5 || warp == 6) {
            mbar_wait(sbase + BAR_CHAIN + 7 * 8);
            uint4 ov[4];
            uint2 ml[4];
#pragma unroll
            for (int s = 0; s < 4; s++) { ov[s] = make_uint4(EMPTY, EMPTY, EMPTY, EMPTY); ml[s] = make_uint2(EMPTY, EMPTY); }
            int spin = 0;
            while (true) {
                uint32_t mx = 0;
#pragma unroll
                for (int s = 0; s < 4; s++) { repoll4(ov[s], x3src + s * 264 + lane * 4); repoll2(ml[s], x3src + s * 264 + 128); }
#pragma unroll
                for (int s = 0; s < 4; s++) mx = max(mx, max(umax4(ov[s]), max(ml[s].x, ml[s].y)));
                if (__all_sync(FULLM, mx != EMPTY)) break;
                if (++spin > SPIN_LIMIT) __trap();
            }
            const float M = fmaxf(fmaxf(__uint_as_float(ml[0].x), __uint_as_float(ml[1].x)), fmaxf(__uint_as_float(ml[2].x), __uint_as_float(ml[3].x)));
            float o0 = 0.f, o1 = 0.f, o2 = 0.f, o3 = 0.f, L = 0.f;
#pragma unroll
            for (int s = 0; s < 4; s++) {
                const float f = ex2((__uint_as_float(ml[s].x) - M) * kLog2e);
                o0 = fmaf(f, __uint_as_float(ov[s].x), o0);
                o1 = fmaf(f, __uint_as_float(ov[s].y), o1);
                o2 = fmaf(f, __uint_as_float(ov[s].z), o2);
                o3 = fmaf(f, __uint_as_float(ov[s].w), o3);
                L = fmaf(f, __uint_as_float(ml[s].y), L);
            }
            const float rlv = frcp(L);
            *reinterpret_cast<uint2*>(smem + SM_QS + (warp & 1) * 256 + lane * 8) = make_uint2(pack_bf(o0 * rlv, o1 * rlv), pack_bf(o2 * rlv, o3 * rlv));
        }
        mbar_wait(bar_full + (NKV + (lane & 1)) * 8);
#pragma unroll
        for (int ks = 0; ks < 8; ks++) ldsm4t(tla + OFF_WO + ks * 16 * 288, w[ks]);
        if (warp == 0) {
#pragma unroll
            for (int ks = 0; ks < 8; ks++) ldsm4t(tla + OFF_WO + 256 + ks * 16 * 288, w9[ks]);
        }
        cons_bar();
        uint32_t b[16];
#pragma unroll
        for (int k = 0; k < 16; k++) b[k] = __float_as_uint(lds1(osa + k * 16));
        if (warp == 0) TS(5);
        float c[2][4] = {{0.f, 0.f, 0.f, 0.f}, {0.f, 0.f, 0.f, 0.f}};
#pragma unroll
        for (int ks = 0; ks < 8; ks++) mma16816(c[ks & 1], w[ks][0], w[ks][1], w[ks][2], w[ks][3], b[2 * ks], b[2 * ks + 1]);
        {
            const float v0 = (t & 2) ? ((t & 1) ? c[0][3] : c[0][2]) : ((t & 1) ? c[0][1] : c[0][0]);
            const float v1 = (t & 2) ? ((t & 1) ? c[1][3] : c[1][2]) : ((t & 1) ? c[1][1] : c[1][0]);
            st_rlx1_p(xdst, canon(v0 + v1), true);
        }
        if (warp == 0) {
            float e[2][4] = {{0.f, 0.f, 0.f, 0.f}, {0.f, 0.f, 0.f, 0.f}};
#pragma unroll
            for (int ks = 0; ks < 8; ks++) mma16816(e[ks & 1], w9[ks][0], w9[ks][1], w9[ks][2], w9[ks][3], b[2 * ks], b[2 * ks + 1]);
            const float v0 = (t & 2) ? ((t & 1) ? e[0][3] : e[0][2]) : ((t & 1) ? e[0][1] : e[0][0]);
            const float v1 = (t & 2) ? ((t & 1) ? e[1][3] : e[1][2]) : ((t & 1) ? e[1][1] : e[1][0]);
            st_rlx1_p(xdst + 16 * 256, canon(v0 + v1), true);
        }
    }
    if (warp == 0) TS(22);
    float o_x1 = 0.f;
    if (owner) {
        const float s = owner_sum(osrc, lane);
        o_x1 = bfr(o_x + bfr(o_ga * bfr(s)));
        const float nb = __shfl_xor_sync(FULLM, o_x1, 4);
        uint32_t u = (lane & 4) ? pack_bf(nb, o_x1) : pack_bf(o_x1, nb);
        if (u == EMPTY) u = 0x7FFF7FFFu;
        st_rlx1_p(x5dst, u, true);
    }
    if (tid == 0) mbar_arrive(sbase + BAR_GATE);
    if (warp == 0) TS(6);
    {
        uint32_t w[2][9][4], w9[9][4];
        mbar_wait(bar_full + (NKV + 2 + (lane & 3)) * 8);
#pragma unroll
        for (int ks = 0; ks < 9; ks++) {
            ldsm4t(tla + OFF_W1 + ks * 16 * 288, w[0][ks]);
            ldsm4t(tla + OFF_W3 + ks * 16 * 288, w[1][ks]);
        }
        if (warp == 1 || warp == 7) {
            const uint32_t a = tla + (warp == 1 ? OFF_W1 + 7 * 32 : OFF_W3 + 32);
#pragma unroll
            for (int ks = 0; ks < 9; ks++) ldsm4t(a + ks * 16 * 288, w9[ks]);
        }
        if (warp >= 2 && warp < 7) {
            const unsigned* p = x5src;
            uint4 v = make_uint4(EMPTY, EMPTY, EMPTY, EMPTY);
            int spin = 0;
            if (warp == 3) {
                while (true) {
                    if (lane == 0) repoll4(v, p);
                    if (__any_sync(FULLM, umax4(v) != EMPTY)) break;
                    if (++spin > SPIN_LIMIT) __trap();
                }
                if (lane == 0) mbar_arrive(sbase + BAR_SENT);
            } else {
                mbar_wait(sbase + BAR_SENT);
            }
            while (true) {
                repoll4(v, p);
                if (__all_sync(FULLM, umax4(v) != EMPTY)) break;
                if (++spin > SPIN_LIMIT) __trap();
            }
            asm volatile("st.shared.v4.u32 [%0], {%1,%2,%3,%4};" ::"r"(x5sts), "r"(v.x), "r"(v.y), "r"(v.z), "r"(v.w) : "memory");
        }
        cons_bar();
        uint2 xv[9];
        uint32_t h2[18];
#pragma unroll
        for (int i = 0; i < 9; i++) xv[i] = lds2(xa0 + i * 8);
#pragma unroll
        for (int i = 0; i < 18; i++) h2[i] = __float_as_uint(lds1(xb0 + i * 16));
        if (warp == 0) TS(7);
        float st[3][4];
#pragma unroll
        for (int k = 0; k < 3; k++) { st[k][0] = st[k][1] = st[k][2] = st[k][3] = 0.f; }
#pragma unroll
        for (int i = 0; i < 9; i++) mma16816(st[i % 3], xv[i].x, 0x3F803F80u, xv[i].y, 0x3F803F80u, xv[i].x, xv[i].y);
        float sm = (g & 1) ? (st[0][3] + st[1][3]) + st[2][3] : (st[0][2] + st[1][2]) + st[2][2];
        float sq = (g & 1) ? (st[0][1] + st[1][1]) + st[2][1] : (st[0][0] + st[1][0]) + st[2][0];
        sq = (t == (g >> 1)) ? sq : 0.f;
        sm += __shfl_xor_sync(FULLM, sm, 1);
        sq += __shfl_xor_sync(FULLM, sq, 1);
        sm += __shfl_xor_sync(FULLM, sm, 2);
        sq += __shfl_xor_sync(FULLM, sq, 2);
        sq += __shfl_xor_sync(FULLM, sq, 8);
        sq += __shfl_xor_sync(FULLM, sq, 16);
        float mean = sm * (1.0f / kD);
        const float var = fmaf(-mean, mean, sq * (1.0f / kD));
        float rs = frcp(bfr(fsqrt(bfr(bfr(var) + 1e-5f))));
        if (__any_sync(FULLM, !(mean * mean <= 8.0f * var) || !(var < 1e30f))) ln_stats(xv, mean, rs);
        const uint32_t mb2 = pack_bf(mean, mean);
#pragma unroll
        for (int i = 0; i < 18; i++) {
            const uint32_t d = bsub2(h2[i], mb2);
            h2[i] = badd2(bmul2(pack_bf(bf_lo(d) * rs, bf_hi(d) * rs), c12[i]), sh2[i]);
        }
        float c[2][2][4];
#pragma unroll
        for (int m = 0; m < 4; m++) { c[m >> 1][m & 1][0] = c[m >> 1][m & 1][1] = c[m >> 1][m & 1][2] = c[m >> 1][m & 1][3] = 0.f; }
#pragma unroll
        for (int ks = 0; ks < 9; ks++)
#pragma unroll
            for (int m = 0; m < 2; m++) mma16816(c[m][ks & 1], w[m][ks][0], w[m][ks][1], w[m][ks][2], w[m][ks][3], h2[2 * ks], h2[2 * ks + 1]);
        st_rlx1_p(x7dst, canon(pick(c[0][0], t) + pick(c[0][1], t)), true);
        st_rlx1_p(x7dst + 288, canon(pick(c[1][0], t) + pick(c[1][1], t)), true);
        if (warp == 1 || warp == 7) {
            float e[3][4] = {{0.f, 0.f, 0.f, 0.f}, {0.f, 0.f, 0.f, 0.f}, {0.f, 0.f, 0.f, 0.f}};
#pragma unroll
            for (int ks = 0; ks < 9; ks++) mma16816(e[ks % 3], w9[ks][0], w9[ks][1], w9[ks][2], w9[ks][3], h2[2 * ks], h2[2 * ks + 1]);
            st_rlx1_p(x7dst + (warp == 1 ? 112 : 288 + 16), canon((pick(e[0], t) + pick(e[1], t)) + pick(e[2], t)), true);
        }
    }
    if (warp == 0) TS(16);
    {
        if (warp < 5) {
            uint2 gv[4], uv[4];
#pragma unroll
            for (int k = 0; k < 4; k++) { gv[k] = make_uint2(EMPTY, EMPTY); uv[k] = make_uint2(EMPTY, EMPTY); }
            int spin = 0;
            while (true) {
                uint32_t mx = 0;
#pragma unroll
                for (int k = 0; k < 4; k++) { repoll2(gv[k], hsrc + k * 576); repoll2(uv[k], hsrc + k * 576 + 288); }
#pragma unroll
                for (int k = 0; k < 4; k++) mx = max(mx, max(max(gv[k].x, gv[k].y), max(uv[k].x, uv[k].y)));
                if (__all_sync(FULLM, mx != EMPTY)) break;
                if (++spin > SPIN_LIMIT) __trap();
            }
            const float g0 = (__uint_as_float(gv[0].x) + __uint_as_float(gv[1].x)) + (__uint_as_float(gv[2].x) + __uint_as_float(gv[3].x));
            const float g1 = (__uint_as_float(gv[0].y) + __uint_as_float(gv[1].y)) + (__uint_as_float(gv[2].y) + __uint_as_float(gv[3].y));
            const float u0 = (__uint_as_float(uv[0].x) + __uint_as_float(uv[1].x)) + (__uint_as_float(uv[2].x) + __uint_as_float(uv[3].x));
            const float u1 = (__uint_as_float(uv[0].y) + __uint_as_float(uv[1].y)) + (__uint_as_float(uv[2].y) + __uint_as_float(uv[3].y));
            reinterpret_cast<uint32_t*>(smem + SM_HH)[ht] = bmul2(pack_bf(silu_f(bfr(g0)), silu_f(bfr(g1))), pack_bf(u0, u1));
        }
        uint32_t w[9][4], w9[9][4];
        mbar_wait(bar_full + (NKV + 6 + (lane & 1)) * 8);
#pragma unroll
        for (int ks = 0; ks < 9; ks++) ldsm4t(tla + OFF_W2 + ks * 16 * 288, w[ks]);
        if (warp == 7) {
#pragma unroll
            for (int ks = 0; ks < 9; ks++) ldsm4t(tla + OFF_W2 + 32 + ks * 16 * 288, w9[ks]);
        }
        cons_bar();
        if (warp == 0) TS(10);
        uint32_t b[18];
#pragma unroll
        for (int k = 0; k < 18; k++) b[k] = __float_as_uint(lds1(hha + k * 16));
        float c[3][4] = {{0.f, 0.f, 0.f, 0.f}, {0.f, 0.f, 0.f, 0.f}, {0.f, 0.f, 0.f, 0.f}};
#pragma unroll
        for (int ks = 0; ks < 9; ks++) mma16816(c[ks % 3], w[ks][0], w[ks][1], w[ks][2], w[ks][3], b[2 * ks], b[2 * ks + 1]);
        st_rlx1_p(xdst + 2 * 72 * 256, canon((pick(c[0], t) + pick(c[1], t)) + pick(c[2], t)), true);
        if (warp == 7) {
            float e[3][4] = {{0.f, 0.f, 0.f, 0.f}, {0.f, 0.f, 0.f, 0.f}, {0.f, 0.f, 0.f, 0.f}};
#pragma unroll
            for (int ks = 0; ks < 9; ks++) mma16816(e[ks % 3], w9[ks][0], w9[ks][1], w9[ks][2], w9[ks][3], b[2 * ks], b[2 * ks + 1]);
            st_rlx1_p(xdst + 2 * 72 * 256 + 2 * 256, canon((pick(e[0], t) + pick(e[1], t)) + pick(e[2], t)), true);
        }
    }
    if (warp == 0) TS(11);
    if (owner) {
        const float s = owner_sum(osrc + 2 * 72 * 256, lane);
        const float r = o_x1 + bfr(o_gb * bfr(s));
        if (lane < 8) *outp = __float2bfloat16_rn(r);
        if (warp == 0) TS(12);
    }
}

__device__ float f_a[2 * kF], f_mod[2 * kMOD], f_q[2 * kQD], f_o[2 * kQD], f_t[2 * kD], f_x1[2 * kD], f_g[2 * kF], f_u[2 * kF];

__global__ void fb_gemv(const float* a, const bf16* W, float* o, int K, int N) {
    const int n = blockIdx.x * blockDim.x + threadIdx.x;
    if (n >= N) return;
    float s0 = 0.f, s1 = 0.f;
    for (int k = 0; k < K; k++) {
        const float w = __bfloat162float(W[(size_t)k * N + n]);
        s0 = fmaf(a[k], w, s0);
        s1 = fmaf(a[K + k], w, s1);
    }
    o[n] = bfr(s0);
    o[N + n] = bfr(s1);
}
__global__ void fb_silu_c(const bf16* c) {
    const int i = blockIdx.x * blockDim.x + threadIdx.x;
    if (i < 2 * kD) f_a[i] = bfr(silu_f(__bfloat162float(c[i])));
}
__global__ void fb_ln(const bf16* x, int stage) {
    __shared__ float v[kD], red[2];
    const int b = blockIdx.x, n = threadIdx.x;
    const float* mod = f_mod + b * kMOD;
    float xv = __bfloat162float(x[b * kD + n]);
    if (stage) { xv = bfr(xv + bfr(mod[2 * kD + n] * f_t[b * kD + n])); f_x1[b * kD + n] = xv; }
    v[n] = xv;
    __syncthreads();
    if (n == 0) {
        float s = 0.f, q = 0.f;
        for (int i = 0; i < kD; i++) s += v[i];
        s *= 1.0f / kD;
        for (int i = 0; i < kD; i++) q += (v[i] - s) * (v[i] - s);
        red[0] = bfr(s);
        red[1] = bfr(sqrtf(bfr(bfr(q * (1.0f / kD)) + 1e-5f)));
    }
    __syncthreads();
    const float ln = bfr(bfr(xv - red[0]) / red[1]);
    f_a[b * kD + n] = bfr(bfr(ln * bfr(1.0f + mod[(stage ? 4 : 1) * kD + n])) + mod[(stage ? 3 : 0) * kD + n]);
}
__global__ void fb_attn(const bf16* kc, const bf16* vc) {
    __shared__ float sc[kSK], red[128];
    const int b = blockIdx.x >> 5, h = blockIdx.x & 31, d = threadIdx.x;
    const size_t base = (size_t)(b * 16 + (h >> 1)) * kSK * 128;
    const float* q = f_q + b * kQD + h * 128;
    float mx = -INFINITY;
    for (int k = d; k < kSK; k += 128) {
        float s = 0.f;
        for (int i = 0; i < 128; i++) s = fmaf(q[i], __bfloat162float(kc[base + (size_t)k * 128 + i]), s);
        s = bfr(bfr(s) * kScale);
        sc[k] = s;
        mx = fmaxf(mx, s);
    }
    red[d] = mx;
    __syncthreads();
    for (int i = 0; i < 128; i++) mx = fmaxf(mx, red[i]);
    __syncthreads();
    float l = 0.f;
    for (int k = d; k < kSK; k += 128) { const float p = expf(sc[k] - mx); sc[k] = p; l += p; }
    red[d] = l;
    __syncthreads();
    l = 0.f;
    for (int i = 0; i < 128; i++) l += red[i];
    float o = 0.f;
    for (int k = 0; k < kSK; k++) o = fmaf(bfr(sc[k] / l), __bfloat162float(vc[base + (size_t)k * 128 + d]), o);
    f_o[b * kQD + h * 128 + d] = bfr(o);
}
__global__ void fb_hh() {
    const int i = blockIdx.x * blockDim.x + threadIdx.x;
    if (i < 2 * kF) f_a[i] = bfr(bfr(silu_f(f_g[i])) * f_u[i]);
}
__global__ void fb_out(bf16* out) {
    const int i = blockIdx.x * blockDim.x + threadIdx.x;
    if (i < 2 * kD) out[i] = __float2bfloat16_rn(f_x1[i] + bfr(f_mod[(i / kD) * kMOD + 5 * kD + i % kD] * f_t[i]));
}
template <class T> T* sym(T& v) { void* p = nullptr; cudaGetSymbolAddress(&p, v); return reinterpret_cast<T*>(p); }

typedef CUresult (*EncodeTiledFn)(CUtensorMap*, CUtensorMapDataType, cuuint32_t, void*, const cuuint64_t*, const cuuint64_t*,
                                  const cuuint32_t*, const cuuint32_t*, CUtensorMapInterleave, CUtensorMapSwizzle,
                                  CUtensorMapL2promotion, CUtensorMapFloatOOBfill);

}

extern "C" void kernel_launch(void* const* d_in, const int* in_sizes, int n_in, void* d_out, int out_size) {
    (void)in_sizes; (void)n_in; (void)out_size;
    static EncodeTiledFn enc = nullptr;
    static int fast = -1;
    if (fast < 0) {
        void* fn = nullptr;
        cudaDriverEntryPointQueryResult qr;
        cudaGetDriverEntryPoint("cuTensorMapEncodeTiled", &fn, cudaEnableDefault, &qr);
        enc = (EncodeTiledFn)fn;
        int dev = 0, sms = 0, occ = 0;
        cudaGetDevice(&dev);
        cudaDeviceGetAttribute(&sms, cudaDevAttrMultiProcessorCount, dev);
        const cudaError_t e = cudaFuncSetAttribute(fused_kernel, cudaFuncAttributeMaxDynamicSharedMemorySize, SM_TOTAL);
        cudaOccupancyMaxActiveBlocksPerMultiprocessor(&occ, fused_kernel, NTHR, SM_TOTAL);
        fast = (enc && e == cudaSuccess && sms * occ >= NCTA) ? 1 : 0;
        (void)cudaGetLastError();
    }
    const bf16* x    = (const bf16*)d_in[0];
    const bf16* kc   = (const bf16*)d_in[1];
    const bf16* vc   = (const bf16*)d_in[2];
    void* wq         = d_in[3];
    void* wo         = d_in[4];
    void* w1         = d_in[6];
    void* w3         = d_in[7];
    void* w2         = d_in[8];
    const bf16* cvec = (const bf16*)d_in[9];
    const bf16* wmod = (const bf16*)d_in[10];

    if (!fast) {
        float *a = (float*)sym(f_a), *mod = (float*)sym(f_mod), *q = (float*)sym(f_q), *o = (float*)sym(f_o), *t = (float*)sym(f_t),
              *gt = (float*)sym(f_g), *up = (float*)sym(f_u);
        fb_silu_c<<<9, 128>>>(cvec);
        fb_gemv<<<kMOD / 64, 64>>>(a, wmod, mod, kD, kMOD);
        fb_ln<<<2, kD>>>(x, 0);
        fb_gemv<<<kQD / 64, 64>>>(a, (const bf16*)wq, q, kD, kQD);
        fb_attn<<<64, 128>>>(kc, vc);
        fb_gemv<<<kD / 64, 64>>>(o, (const bf16*)wo, t, kQD, kD);
        fb_ln<<<2, kD>>>(x, 1);
        fb_gemv<<<kF / 64, 64>>>(a, (const bf16*)w1, gt, kD, kF);
        fb_gemv<<<kF / 64, 64>>>(a, (const bf16*)w3, up, kD, kF);
        fb_hh<<<2 * kF / 128, 128>>>();
        fb_gemv<<<kD / 64, 64>>>(a, (const bf16*)w2, t, kF, kD);
        fb_out<<<9, 128>>>((bf16*)d_out);
        return;
    }

    CUtensorMap tm1, tm3, tmo, tm2, tmq, tmm;
    const cuuint64_t dims[2] = {(cuuint64_t)kF, (cuuint64_t)kD};
    const cuuint64_t strides[1] = {(cuuint64_t)kF * 2};
    const cuuint32_t box[2] = {144, 72};
    const cuuint32_t es[2] = {1, 1};
    enc(&tm1, CU_TENSOR_MAP_DATA_TYPE_BFLOAT16, 2, w1, dims, strides, box, es, CU_TENSOR_MAP_INTERLEAVE_NONE,
        CU_TENSOR_MAP_SWIZZLE_NONE, CU_TENSOR_MAP_L2_PROMOTION_L2_128B, CU_TENSOR_MAP_FLOAT_OOB_FILL_NONE);
    enc(&tm3, CU_TENSOR_MAP_DATA_TYPE_BFLOAT16, 2, w3, dims, strides, box, es, CU_TENSOR_MAP_INTERLEAVE_NONE,
        CU_TENSOR_MAP_SWIZZLE_NONE, CU_TENSOR_MAP_L2_PROMOTION_L2_128B, CU_TENSOR_MAP_FLOAT_OOB_FILL_NONE);

    const cuuint64_t odims[2] = {(cuuint64_t)kD, (cuuint64_t)kQD}, dims2[2] = {(cuuint64_t)kD, (cuuint64_t)kF};
    const cuuint32_t lbox[2] = {64, 72};
    const cuuint64_t ostr[1] = {(cuuint64_t)kD * 2};
    const cuuint32_t obox[2] = {144, 64};
    enc(&tmo, CU_TENSOR_MAP_DATA_TYPE_BFLOAT16, 2, wo, odims, ostr, obox, es, CU_TENSOR_MAP_INTERLEAVE_NONE,
        CU_TENSOR_MAP_SWIZZLE_NONE, CU_TENSOR_MAP_L2_PROMOTION_L2_128B, CU_TENSOR_MAP_FLOAT_OOB_FILL_NONE);
    enc(&tm2, CU_TENSOR_MAP_DATA_TYPE_BFLOAT16, 2, w2, dims2, ostr, box, es, CU_TENSOR_MAP_INTERLEAVE_NONE,
        CU_TENSOR_MAP_SWIZZLE_NONE, CU_TENSOR_MAP_L2_PROMOTION_L2_128B, CU_TENSOR_MAP_FLOAT_OOB_FILL_NONE);
    const cuuint64_t qdims[2] = {(cuuint64_t)kQD, (cuuint64_t)kD};
    const cuuint64_t qstr[1] = {(cuuint64_t)kQD * 2};
    enc(&tmq, CU_TENSOR_MAP_DATA_TYPE_BFLOAT16, 2, wq, qdims, qstr, lbox, es, CU_TENSOR_MAP_INTERLEAVE_NONE,
        CU_TENSOR_MAP_SWIZZLE_128B, CU_TENSOR_MAP_L2_PROMOTION_L2_128B, CU_TENSOR_MAP_FLOAT_OOB_FILL_NONE);
    const cuuint64_t mdims[2] = {(cuuint64_t)kMOD, (cuuint64_t)kD};
    const cuuint64_t mstr[1] = {(cuuint64_t)kMOD * 2};
    const cuuint32_t mbox[2] = {32, 144};
    enc(&tmm, CU_TENSOR_MAP_DATA_TYPE_BFLOAT16, 2, (void*)wmod, mdims, mstr, mbox, es, CU_TENSOR_MAP_INTERLEAVE_NONE,
        CU_TENSOR_MAP_SWIZZLE_64B, CU_TENSOR_MAP_L2_PROMOTION_L2_128B, CU_TENSOR_MAP_FLOAT_OOB_FILL_NONE);

    fused_kernel<<<NCTA, NTHR, SM_TOTAL>>>(tm1, tm3, tmo, tm2, tmq, tmm, x, kc, vc, cvec, wmod, (bf16*)d_out);
}
```
